```python
import torch

def _softmax(x, axis=-1):
    return torch.softmax(x, dim=axis)

def _gelu(x):
    return torch.nn.functional.gelu(x, approximate='tanh')

def _silu(x):
    return torch.nn.functional.silu(x)

def _sigmoid(x):
    return torch.sigmoid(x)

def _layernorm(x, axis=-1, eps=1e-05):
    m = x.mean(dim=axis, keepdim=True)
    v = x.var(dim=axis, keepdim=True, unbiased=False)
    return (x - m) / torch.sqrt(v + eps)

def _scatter_add(tgt, idx, src, axis=0):
    return tgt.clone().index_add_(axis, idx, src)

def _segment_sum(src, seg, n):
    out = torch.zeros((n,) + src.shape[1:], dtype=src.dtype)
    return out.index_add_(0, seg, src)

def _pad(x, pw):
    flat = tuple((v for pair in reversed(pw) for v in pair))
    return torch.nn.functional.pad(x, flat)
kernel_name = 'concat_heads__ssm_conv_s5__memory_aug_recurrent_mem_tr__prompt'

def setup_inputs():

    _w = lambda a: (lambda t: t.to(torch.bfloat16) if t.is_floating_point() else t)(torch.as_tensor(a))

    def _A_setup():
        B, S, D = (1, 2048, 576)
        P = D
        Lambda_re = -0.5 * (lambda _x: torch.exp(torch.as_tensor(_x)))((lambda *s: torch.randn(*s, dtype=torch.bfloat16) * 0.8)(P))
        Lambda_im = (lambda *s: torch.randn(*s, dtype=torch.bfloat16) * 0.8)(P) * 1.0
        B_re = (lambda *s: torch.randn(*s, dtype=torch.bfloat16) * 0.8)(P, D) * D ** (-0.5)
        B_im = (lambda *s: torch.randn(*s, dtype=torch.bfloat16) * 0.8)(P, D) * D ** (-0.5)
        C_re = (lambda *s: torch.randn(*s, dtype=torch.bfloat16) * 0.8)(D, P) * P ** (-0.5)
        C_im = (lambda *s: torch.randn(*s, dtype=torch.bfloat16) * 0.8)(D, P) * P ** (-0.5)
        log_dt = (lambda *s: torch.randn(*s, dtype=torch.bfloat16) * 0.8)(P) * 0.3 - 2.0
        Dskip = (lambda *s: torch.randn(*s, dtype=torch.bfloat16) * 0.8)(D)
        return {'x': _w((lambda *s: torch.randn(*s, dtype=torch.bfloat16) * 0.05)(B, S, D)), 'Lambda_re': _w(Lambda_re), 'Lambda_im': _w(Lambda_im), 'B_re': _w(B_re), 'B_im': _w(B_im), 'C_re': _w(C_re), 'C_im': _w(C_im), 'log_dt': _w(log_dt), 'Dskip': _w(Dskip)}
    _A_in = _A_setup()

    def _B_setup():
        B, S, Dm = (1, 2048, 576)
        H, Dh = (32, 128)
        M, seg = (8, 32)
        seg = min(seg, S)
        S = S // seg * seg
        return {'x': _w((lambda *s: torch.randn(*s, dtype=torch.bfloat16) * 0.05)(B, S, Dm)), 'mem0': _w((lambda *s: torch.randn(*s, dtype=torch.bfloat16) * 0.8)(B, M, Dm)), 'Wq': _w((lambda *s: torch.randn(*s, dtype=torch.bfloat16) * 1.6)(Dm, H, Dh) * Dm ** (-0.5)), 'Wk': _w((lambda *s: torch.randn(*s, dtype=torch.bfloat16) * 1.6)(Dm, H, Dh) * Dm ** (-0.5)), 'Wv': _w((lambda *s: torch.randn(*s, dtype=torch.bfloat16) * 0.8)(Dm, H, Dh) * Dm ** (-0.5)), 'Wo': _w((lambda *s: torch.randn(*s, dtype=torch.bfloat16) * 0.8)(H, Dh, Dm) * (H * Dh) ** (-0.5)), 'seg_len': seg}
    _B_in = _B_setup()
    return {'A_x': _A_in['x'], 'A_Lambda_re': _A_in['Lambda_re'], 'A_Lambda_im': _A_in['Lambda_im'], 'A_B_re': _A_in['B_re'], 'A_B_im': _A_in['B_im'], 'A_C_re': _A_in['C_re'], 'A_C_im': _A_in['C_im'], 'A_log_dt': _A_in['log_dt'], 'A_Dskip': _A_in['Dskip'], 'B_x': _B_in['x'], 'B_mem0': _B_in['mem0'], 'B_Wq': _B_in['Wq'], 'B_Wk': _B_in['Wk'], 'B_Wv': _B_in['Wv'], 'B_Wo': _B_in['Wo'], 'B_seg_len': _B_in['seg_len']}

def reference(A_x, A_Lambda_re, A_Lambda_im, A_B_re, A_B_im, A_C_re, A_C_im, A_log_dt, A_Dskip, B_x, B_mem0, B_Wq, B_Wk, B_Wv, B_Wo, B_seg_len):

    def _A_ref(x, Lambda_re, Lambda_im, B_re, B_im, C_re, C_im, log_dt, Dskip):
        Bsz, L, H = x.shape
        Lam = Lambda_re + 1j * Lambda_im
        Bmat = B_re + 1j * B_im
        Cmat = C_re + 1j * C_im
        dt = torch.exp(log_dt)
        Lam_bar = torch.exp(dt * Lam)
        B_bar = ((Lam_bar - 1.0) / Lam)[:, None] * Bmat
        Bu = torch.einsum('bld,pd->blp', x + 0j, B_bar)
        h = torch.zeros_like(Bu[:, 0, :])
        hs = []
        for t in range(L):
            h = Lam_bar[None, :] * h + Bu[:, t, :]
            hs.append(h)
        hseq = torch.stack(hs, 1)
        y = 2.0 * torch.einsum('blp,dp->bld', hseq, Cmat).real + x * Dskip[None, None, :]
        return y

    def _B_ref(x, mem0, Wq, Wk, Wv, Wo, seg_len):
        B, S, Dm = x.shape
        H, Dh = (Wq.shape[1], Wq.shape[2])
        M = mem0.shape[1]
        scale = Dh ** (-0.5)
        n_seg = S // seg_len
        L = M + seg_len
        idx = torch.arange(L)
        mask = (idx[:, None] < M) | (idx[:, None] >= idx[None, :])
        mem = mem0
        outs = []
        for s in range(n_seg):
            xs = x[:, s * seg_len:(s + 1) * seg_len, :].clone()
            h = torch.concatenate([mem, xs], axis=1)
            q = torch.einsum('btd,dhe->bhte', h, Wq)
            k = torch.einsum('btd,dhe->bhte', h, Wk)
            v = torch.einsum('btd,dhe->bhte', h, Wv)
            scores = torch.einsum('bhqe,bhke->bhqk', q, k) * scale
            scores = torch.where(mask[None, None], scores, -1000000000.0)
            p = _softmax(scores, axis=-1)
            o = torch.einsum('bhqk,bhke->bhqe', p, v)
            o = torch.einsum('bhte,hed->btd', o, Wo)
            mem = o[:, :M, :].clone()
            outs.append(o[:, M:, :])
        return torch.concatenate(outs, axis=1)
    a = _A_ref(A_x, A_Lambda_re, A_Lambda_im, A_B_re, A_B_im, A_C_re, A_C_im, A_log_dt, A_Dskip)
    b = _B_ref(B_x, B_mem0, B_Wq, B_Wk, B_Wv, B_Wo, B_seg_len)
    return torch.concatenate([a, b], axis=-1)
```

```cpp
#include <cuda_runtime.h>
#include <cuda_bf16.h>
#include <cuda_fp16.h>
#include <cuda.h>
#include <stdint.h>

typedef __nv_bfloat16 bf16;
#define DEVI __device__ __forceinline__
template <int V> struct IC { static constexpr int value = V; };

DEVI uint32_t smem_u32(const void* p) { return (uint32_t)__cvta_generic_to_shared(p); }
DEVI void mbar_init(uint32_t a, uint32_t c) { asm volatile("mbarrier.init.shared::cta.b64 [%0], %1;" ::"r"(a), "r"(c) : "memory"); }
DEVI void mbar_expect(uint32_t a, uint32_t bytes) { asm volatile("mbarrier.arrive.expect_tx.shared::cta.b64 _, [%0], %1;" ::"r"(a), "r"(bytes) : "memory"); }
DEVI void mbar_arrive(uint32_t a) { asm volatile("mbarrier.arrive.shared::cta.b64 _, [%0];" ::"r"(a) : "memory"); }
#define SPIN_LIMIT (1 << 20)
#define MBAR_LIMIT (1 << 18)
DEVI bool spin_fail(int lim, int maxv, uint32_t) { if (lim > maxv) __trap(); return false; }
DEVI void mbar_wait(uint32_t a, uint32_t par) {
  uint32_t ok; int lim = 0;
  do {
    asm volatile("{.reg .pred p; mbarrier.try_wait.parity.shared::cta.b64 p, [%1], %2; selp.u32 %0,1,0,p;}" : "=r"(ok) : "r"(a), "r"(par) : "memory");
  } while (!ok && !spin_fail(++lim, MBAR_LIMIT, a));
}
DEVI void mbar_wait_fast(uint32_t a, uint32_t par) {
  asm volatile("{\n.reg .pred p, q;\n.reg .u32 c;\nmov.u32 c, 0;\n"
               "WAIT_L:\nmbarrier.try_wait.parity.shared::cta.b64 p, [%0], %1;\n"
               "add.u32 c, c, 1;\nsetp.lt.and.u32 q, c, 4194304, !p;\n@q bra.uni WAIT_L;\n@!p trap;\n}" ::"r"(a), "r"(par) : "memory");
}
DEVI void mbar_wait_cl(uint32_t a, uint32_t par) {
  uint32_t ok; int lim = 0;
  do {
    asm volatile("{.reg .pred p; mbarrier.try_wait.parity.acquire.cluster.shared::cta.b64 p, [%1], %2; selp.u32 %0,1,0,p;}" : "=r"(ok) : "r"(a), "r"(par) : "memory");
  } while (!ok && !spin_fail(++lim, MBAR_LIMIT, a));
}
DEVI void bar_sync(int id, int n) { asm volatile("bar.sync %0, %1;" ::"r"(id), "r"(n) : "memory"); }
DEVI void bar_arrive(int id, int n) { asm volatile("bar.arrive %0, %1;" ::"r"(id), "r"(n) : "memory"); }
DEVI void cluster_arrive() { asm volatile("barrier.cluster.arrive.release.aligned;" ::: "memory"); }
DEVI void cluster_wait() { asm volatile("barrier.cluster.wait.acquire.aligned;" ::: "memory"); }
DEVI void fence_async_smem() { asm volatile("fence.proxy.async.shared::cta;" ::: "memory"); }
DEVI void fence_async_all() { asm volatile("fence.proxy.async;" ::: "memory"); }
DEVI void fence_async_global() { asm volatile("fence.proxy.async.global;" ::: "memory"); }
DEVI float rcp_fast(float x) { float y; asm("rcp.approx.ftz.f32 %0, %1;" : "=f"(y) : "f"(x)); return y; }
DEVI void sts128f(uint32_t a, float x, float y, float z, float w) { asm volatile("st.shared.v4.f32 [%0], {%1,%2,%3,%4};" ::"r"(a), "f"(x), "f"(y), "f"(z), "f"(w) : "memory"); }
DEVI uint32_t mapa(uint32_t a, uint32_t r) { uint32_t o; asm volatile("mapa.shared::cluster.u32 %0, %1, %2;" : "=r"(o) : "r"(a), "r"(r)); return o; }
DEVI uint32_t clk32() { uint32_t c; asm volatile("mov.u32 %0, %%clock;" : "=r"(c)::"memory"); return c; }

DEVI void ldsm4(uint32_t* r, uint32_t a) { asm volatile("ldmatrix.sync.aligned.m8n8.x4.shared.b16 {%0,%1,%2,%3}, [%4];" : "=r"(r[0]), "=r"(r[1]), "=r"(r[2]), "=r"(r[3]) : "r"(a) : "memory"); }
DEVI void ldsm4t(uint32_t* r, uint32_t a) { asm volatile("ldmatrix.sync.aligned.m8n8.x4.trans.shared.b16 {%0,%1,%2,%3}, [%4];" : "=r"(r[0]), "=r"(r[1]), "=r"(r[2]), "=r"(r[3]) : "r"(a) : "memory"); }
DEVI void stsm4(uint32_t a, uint32_t r0, uint32_t r1, uint32_t r2, uint32_t r3) { asm volatile("stmatrix.sync.aligned.m8n8.x4.shared.b16 [%0], {%1,%2,%3,%4};" ::"r"(a), "r"(r0), "r"(r1), "r"(r2), "r"(r3) : "memory"); }
DEVI void stsm4t(uint32_t a, uint32_t r0, uint32_t r1, uint32_t r2, uint32_t r3) { asm volatile("stmatrix.sync.aligned.m8n8.x4.trans.shared.b16 [%0], {%1,%2,%3,%4};" ::"r"(a), "r"(r0), "r"(r1), "r"(r2), "r"(r3) : "memory"); }
DEVI void stsm2(uint32_t a, uint32_t r0, uint32_t r1) { asm volatile("stmatrix.sync.aligned.m8n8.x2.shared.b16 [%0], {%1,%2};" ::"r"(a), "r"(r0), "r"(r1) : "memory"); }
DEVI void sts64f(uint32_t a, float x, float y) { asm volatile("st.shared.v2.f32 [%0], {%1,%2};" ::"r"(a), "f"(x), "f"(y) : "memory"); }
DEVI void ldsm2(uint32_t* r, uint32_t a) { asm volatile("ldmatrix.sync.aligned.m8n8.x2.shared.b16 {%0,%1}, [%2];" : "=r"(r[0]), "=r"(r[1]) : "r"(a) : "memory"); }
DEVI uint2 lds64(uint32_t a) { uint2 v; asm volatile("ld.shared.v2.b32 {%0,%1}, [%2];" : "=r"(v.x), "=r"(v.y) : "r"(a) : "memory"); return v; }
DEVI uint2 lds64v(uint32_t a) { uint2 v; asm volatile("ld.volatile.shared.v2.b32 {%0,%1}, [%2];" : "=r"(v.x), "=r"(v.y) : "r"(a) : "memory"); return v; }
DEVI uint4 lds128(uint32_t a) { uint4 v; asm volatile("ld.shared.v4.b32 {%0,%1,%2,%3}, [%4];" : "=r"(v.x), "=r"(v.y), "=r"(v.z), "=r"(v.w) : "r"(a) : "memory"); return v; }
DEVI uint32_t opaque(uint32_t v) { return __shfl_sync(0xffffffffu, v, threadIdx.x & 31); }
DEVI uint32_t and_v(uint32_t a, uint32_t b) { uint32_t r; asm volatile("and.b32 %0, %1, %2;" : "=r"(r) : "r"(a), "r"(b)); return r; }
DEVI uint32_t half_v(uint32_t a) { uint32_t r; asm volatile("shr.u32 %0, %1, 1;" : "=r"(r) : "r"(a)); return r; }
DEVI uint32_t babsmax2(uint32_t a, uint32_t b) {
  __nv_bfloat162 r = __hmax2(__habs2(*reinterpret_cast<__nv_bfloat162*>(&a)), __habs2(*reinterpret_cast<__nv_bfloat162*>(&b)));
  return *reinterpret_cast<uint32_t*>(&r);
}
DEVI uint32_t habsmax2(uint32_t a, uint32_t b) {
  __half2 r = __hmax2(__habs2(*reinterpret_cast<__half2*>(&a)), __habs2(*reinterpret_cast<__half2*>(&b)));
  return *reinterpret_cast<uint32_t*>(&r);
}
DEVI void sts64(uint32_t a, uint32_t x, uint32_t y) { asm volatile("st.shared.v2.b32 [%0], {%1,%2};" ::"r"(a), "r"(x), "r"(y) : "memory"); }
DEVI void sts32(uint32_t a, uint32_t v) { asm volatile("st.shared.b32 [%0], %1;" ::"r"(a), "r"(v) : "memory"); }
DEVI uint32_t lds32(uint32_t a) { uint32_t v; asm volatile("ld.shared.b32 %0, [%1];" : "=r"(v) : "r"(a) : "memory"); return v; }
DEVI float2 lds64f(uint32_t a) { float2 v; asm volatile("ld.shared.v2.f32 {%0,%1}, [%2];" : "=f"(v.x), "=f"(v.y) : "r"(a) : "memory"); return v; }
DEVI float4 lds128f(uint32_t a) { float4 v; asm volatile("ld.shared.v4.f32 {%0,%1,%2,%3}, [%4];" : "=f"(v.x), "=f"(v.y), "=f"(v.z), "=f"(v.w) : "r"(a) : "memory"); return v; }

DEVI void mma16(float* d, const uint32_t* a, uint32_t b0, uint32_t b1) {
  asm volatile("mma.sync.aligned.m16n8k16.row.col.f32.bf16.bf16.f32 {%0,%1,%2,%3}, {%4,%5,%6,%7}, {%8,%9}, {%0,%1,%2,%3};"
               : "+f"(d[0]), "+f"(d[1]), "+f"(d[2]), "+f"(d[3]) : "r"(a[0]), "r"(a[1]), "r"(a[2]), "r"(a[3]), "r"(b0), "r"(b1));
}
DEVI void mma16r(float* d, uint32_t a0, uint32_t a1, uint32_t a2, uint32_t a3, uint32_t b0, uint32_t b1) {
  asm volatile("mma.sync.aligned.m16n8k16.row.col.f32.bf16.bf16.f32 {%0,%1,%2,%3}, {%4,%5,%6,%7}, {%8,%9}, {%0,%1,%2,%3};"
               : "+f"(d[0]), "+f"(d[1]), "+f"(d[2]), "+f"(d[3]) : "r"(a0), "r"(a1), "r"(a2), "r"(a3), "r"(b0), "r"(b1));
}
DEVI void mma16z(float* d, uint32_t a0, uint32_t a1, uint32_t a2, uint32_t a3, uint32_t b0, uint32_t b1) {
  asm volatile("mma.sync.aligned.m16n8k16.row.col.f32.bf16.bf16.f32 {%0,%1,%2,%3}, {%4,%5,%6,%7}, {%8,%9}, {%10,%10,%10,%10};"
               : "=f"(d[0]), "=f"(d[1]), "=f"(d[2]), "=f"(d[3]) : "r"(a0), "r"(a1), "r"(a2), "r"(a3), "r"(b0), "r"(b1), "f"(0.f));
}
DEVI void mma8(float* d, uint32_t a0, uint32_t a1, uint32_t b0) {
  asm volatile("mma.sync.aligned.m16n8k8.row.col.f32.bf16.bf16.f32 {%0,%1,%2,%3}, {%4,%5}, {%6}, {%0,%1,%2,%3};"
               : "+f"(d[0]), "+f"(d[1]), "+f"(d[2]), "+f"(d[3]) : "r"(a0), "r"(a1), "r"(b0));
}
DEVI void mma8z(float* d, uint32_t a0, uint32_t a1, uint32_t b0) {
  asm volatile("mma.sync.aligned.m16n8k8.row.col.f32.bf16.bf16.f32 {%0,%1,%2,%3}, {%4,%5}, {%6}, {%7,%7,%7,%7};"
               : "=f"(d[0]), "=f"(d[1]), "=f"(d[2]), "=f"(d[3]) : "r"(a0), "r"(a1), "r"(b0), "f"(0.f));
}
DEVI uint32_t pack_bf16(float lo, float hi) { uint32_t r; asm("cvt.rn.bf16x2.f32 %0, %1, %2;" : "=r"(r) : "f"(hi), "f"(lo)); return r; }
DEVI uint32_t pack_f16(float lo, float hi) { uint32_t r; asm("cvt.rn.f16x2.f32 %0, %1, %2;" : "=r"(r) : "f"(hi), "f"(lo)); return r; }
DEVI uint32_t h2b(uint32_t h) { float2 f = __half22float2(*reinterpret_cast<const __half2*>(&h)); return pack_bf16(f.x, f.y); }
DEVI float ex2(float x) { float y; asm("ex2.approx.ftz.f32 %0, %1;" : "=f"(y) : "f"(x)); return y; }
DEVI float bf_lo(uint32_t v) { return __uint_as_float(v << 16); }
DEVI float bf_hi(uint32_t v) { return __uint_as_float(v & 0xffff0000u); }

DEVI void st_async32(uint32_t a, uint32_t v, uint32_t mb) { asm volatile("st.async.shared::cluster.mbarrier::complete_tx::bytes.b32 [%0], %1, [%2];" ::"r"(a), "r"(v), "r"(mb) : "memory"); }
DEVI void st_async64(uint32_t a, uint32_t x, uint32_t y, uint32_t mb) { asm volatile("st.async.shared::cluster.mbarrier::complete_tx::bytes.v2.b32 [%0], {%1,%2}, [%3];" ::"r"(a), "r"(x), "r"(y), "r"(mb) : "memory"); }
DEVI void st_async64f(uint32_t a, float x, float y, uint32_t mb) { asm volatile("st.async.shared::cluster.mbarrier::complete_tx::bytes.v2.f32 [%0], {%1,%2}, [%3];" ::"r"(a), "f"(x), "f"(y), "r"(mb) : "memory"); }
DEVI void st_async128f(uint32_t a, float x, float y, float z, float w, uint32_t mb) { asm volatile("st.async.shared::cluster.mbarrier::complete_tx::bytes.v4.f32 [%0], {%1,%2,%3,%4}, [%5];" ::"r"(a), "f"(x), "f"(y), "f"(z), "f"(w), "r"(mb) : "memory"); }

DEVI void tma2d(uint32_t dst, const CUtensorMap* m, int c0, int c1, uint32_t mb) {
  asm volatile("cp.async.bulk.tensor.2d.shared::cluster.global.mbarrier::complete_tx::bytes [%0], [%1, {%3, %4}], [%2];"
               ::"r"(dst), "l"(m), "r"(mb), "r"(c0), "r"(c1) : "memory");
}
DEVI uint64_t policy_evict_first() { uint64_t p; asm volatile("createpolicy.fractional.L2::evict_first.b64 %0, 1.0;" : "=l"(p)); return p; }
DEVI void tma2d_hint(uint32_t dst, const CUtensorMap* m, int c0, int c1, uint32_t mb, uint64_t pol) {
  asm volatile("cp.async.bulk.tensor.2d.shared::cluster.global.mbarrier::complete_tx::bytes.L2::cache_hint [%0], [%1, {%3, %4}], [%2], %5;"
               ::"r"(dst), "l"(m), "r"(mb), "r"(c0), "r"(c1), "l"(pol) : "memory");
}
DEVI void tma2d_mc(uint32_t dst, const CUtensorMap* m, int c0, int c1, uint32_t mb, uint16_t mask) {
  asm volatile("cp.async.bulk.tensor.2d.shared::cluster.global.mbarrier::complete_tx::bytes.multicast::cluster [%0], [%1, {%3, %4}], [%2], %5;"
               ::"r"(dst), "l"(m), "r"(mb), "r"(c0), "r"(c1), "h"(mask) : "memory");
}
DEVI void tma2d_prefetch(const CUtensorMap* m, int c0, int c1) {
  asm volatile("cp.async.bulk.prefetch.tensor.2d.L2.global [%0, {%1, %2}];" ::"l"(m), "r"(c0), "r"(c1) : "memory");
}
DEVI void bulk_g2s(uint32_t dst, const void* src, uint32_t bytes, uint32_t mb) {
  asm volatile("cp.async.bulk.shared::cluster.global.mbarrier::complete_tx::bytes [%0], [%1], %2, [%3];" ::"r"(dst), "l"(src), "r"(bytes), "r"(mb) : "memory");
}
DEVI void bulk_s2c(uint32_t dst, uint32_t src, uint32_t bytes, uint32_t mb) {
  asm volatile("cp.async.bulk.shared::cluster.shared::cta.mbarrier::complete_tx::bytes [%0], [%1], %2, [%3];" ::"r"(dst), "r"(src), "r"(bytes), "r"(mb) : "memory");
}
DEVI void bulk_s2g(void* dst, uint32_t src, uint32_t bytes) {
  asm volatile("cp.async.bulk.global.shared::cta.bulk_group [%0], [%1], %2;" ::"l"(dst), "r"(src), "r"(bytes) : "memory");
}
DEVI void bulk_commit() { asm volatile("cp.async.bulk.commit_group;" ::: "memory"); }
DEVI void bulk_wait0() { asm volatile("cp.async.bulk.wait_group 0;" ::: "memory"); }
DEVI void bulk_wait_read0() { asm volatile("cp.async.bulk.wait_group.read 0;" ::: "memory"); }

DEVI uint4 ld_relaxed_v4(const void* p) { uint4 v; asm volatile("ld.relaxed.gpu.global.v4.u32 {%0,%1,%2,%3}, [%4];" : "=r"(v.x), "=r"(v.y), "=r"(v.z), "=r"(v.w) : "l"(p) : "memory"); return v; }
DEVI uint2 ld_relaxed_v2(const void* p) { uint2 v; asm volatile("ld.relaxed.gpu.global.v2.u32 {%0,%1}, [%2];" : "=r"(v.x), "=r"(v.y) : "l"(p) : "memory"); return v; }
DEVI uint32_t ld_acquire(const uint32_t* p) { uint32_t v; asm volatile("ld.acquire.gpu.global.u32 %0, [%1];" : "=r"(v) : "l"(p) : "memory"); return v; }
DEVI uint32_t ld_relaxed(const uint32_t* p) { uint32_t v; asm volatile("ld.relaxed.gpu.global.u32 %0, [%1];" : "=r"(v) : "l"(p) : "memory"); return v; }
DEVI void red_release_add(uint32_t* p, uint32_t v) { asm volatile("red.release.gpu.global.add.u32 [%0], %1;" ::"l"(p), "r"(v) : "memory"); }
DEVI void red_relaxed_add(uint32_t* p, uint32_t v) { asm volatile("red.relaxed.gpu.global.add.u32 [%0], %1;" ::"l"(p), "r"(v) : "memory"); }
DEVI void red_f16x8(void* p, uint32_t a, uint32_t b, uint32_t c, uint32_t d) {
  asm volatile("red.relaxed.gpu.global.add.noftz.v4.f16x2 [%0], {%1,%2,%3,%4};" ::"l"(p), "r"(a), "r"(b), "r"(c), "r"(d) : "memory");
}

DEVI void cp16(uint32_t dst, const void* src) { asm volatile("cp.async.cg.shared.global [%0], [%1], 16;" ::"r"(dst), "l"(src) : "memory"); }
DEVI void cp_wait_all() { asm volatile("cp.async.wait_all;" ::: "memory"); }
#define WG_FENCE() asm volatile("wgmma.fence.sync.aligned;" ::: "memory")
#define WG_COMMIT() asm volatile("wgmma.commit_group.sync.aligned;" ::: "memory")
#define WG_WAIT(n) asm volatile("wgmma.wait_group.sync.aligned %0;" ::"n"(n) : "memory")
DEVI uint64_t mkdesc(uint32_t saddr, uint32_t lbo, uint32_t sbo) {
  return (uint64_t)((saddr & 0x3FFFF) >> 4) | ((uint64_t)(lbo >> 4) << 16) | ((uint64_t)(sbo >> 4) << 32) | (1ull << 62);
}
DEVI void wg_n32_rs(float* d, const uint32_t* a, uint64_t db, int sc) {
  asm volatile("{.reg .pred p; setp.ne.b32 p, %21, 0;\n"
               "wgmma.mma_async.sync.aligned.m64n32k16.f32.bf16.bf16 {%0,%1,%2,%3,%4,%5,%6,%7,%8,%9,%10,%11,%12,%13,%14,%15}, {%16,%17,%18,%19}, %20, p, 1, 1, 0;}\n"
               : "+f"(d[0]), "+f"(d[1]), "+f"(d[2]), "+f"(d[3]), "+f"(d[4]), "+f"(d[5]), "+f"(d[6]), "+f"(d[7]),
                 "+f"(d[8]), "+f"(d[9]), "+f"(d[10]), "+f"(d[11]), "+f"(d[12]), "+f"(d[13]), "+f"(d[14]), "+f"(d[15])
               : "r"(a[0]), "r"(a[1]), "r"(a[2]), "r"(a[3]), "l"(db), "r"(sc));
}
DEVI void wg_n32_ss_ta(float* d, uint64_t da, uint64_t db, int sc) {
  asm volatile("{.reg .pred p; setp.ne.b32 p, %18, 0;\n"
               "wgmma.mma_async.sync.aligned.m64n32k16.f32.bf16.bf16 {%0,%1,%2,%3,%4,%5,%6,%7,%8,%9,%10,%11,%12,%13,%14,%15}, %16, %17, p, 1, 1, 1, 0;}\n"
               : "+f"(d[0]), "+f"(d[1]), "+f"(d[2]), "+f"(d[3]), "+f"(d[4]), "+f"(d[5]), "+f"(d[6]), "+f"(d[7]),
                 "+f"(d[8]), "+f"(d[9]), "+f"(d[10]), "+f"(d[11]), "+f"(d[12]), "+f"(d[13]), "+f"(d[14]), "+f"(d[15])
               : "l"(da), "l"(db), "r"(sc));
}
DEVI void wg_n32_rs_z(float* d, const uint32_t* a, uint64_t db) {
  asm volatile("{.reg .pred p; setp.ne.b32 p, 0, 0;\n"
               "wgmma.mma_async.sync.aligned.m64n32k16.f32.bf16.bf16 {%0,%1,%2,%3,%4,%5,%6,%7,%8,%9,%10,%11,%12,%13,%14,%15}, {%16,%17,%18,%19}, %20, p, 1, 1, 0;}\n"
               : "=f"(d[0]), "=f"(d[1]), "=f"(d[2]), "=f"(d[3]), "=f"(d[4]), "=f"(d[5]), "=f"(d[6]), "=f"(d[7]),
                 "=f"(d[8]), "=f"(d[9]), "=f"(d[10]), "=f"(d[11]), "=f"(d[12]), "=f"(d[13]), "=f"(d[14]), "=f"(d[15])
               : "r"(a[0]), "r"(a[1]), "r"(a[2]), "r"(a[3]), "l"(db));
}
constexpr int DM = 576, NH = 32, DH = 128, SEG = 32, NSEG = 64, SEQ = 2048;
constexpr int K1_CTAS = 96;

__device__ __align__(8192) unsigned char g_ar[32 * 24576 + 96 * 256];
__device__ __align__(1024) unsigned char g_ox[NSEG * NH * 8192];
__device__ float g_pub[3 * 96];
__device__ uint32_t g_cnt;
__device__ uint32_t g_flags[128];
__device__ uint32_t g_epoch;
#define TR(i)
#define TRP(i)
#define TRV(i, v)
#define TRDUMP()
#define TRG(i)

constexpr uint32_t SM_XB = 0;
constexpr uint32_t SM_W = 73728;
constexpr int KS_SM = 5;
constexpr uint32_t SM_WO = SM_W + 10240;
constexpr uint32_t SM_ST1 = SM_WO + 36864;
constexpr uint32_t SM_VM = SM_WO + 45056;
constexpr uint32_t SM_QM = SM_VM + 8192;
constexpr uint32_t SM_SB = SM_QM + 2048;
constexpr uint32_t SM_OT = SM_SB + 2560;
constexpr uint32_t SM_PX = SM_W + 73728 + 10240;
constexpr uint32_t SM_VX = SM_PX + 32768;
constexpr uint32_t SM_OS = SM_VX;
constexpr uint32_t SM_ST0 = SM_VX + 16384;
constexpr uint32_t SM_PT = SM_ST0;
static_assert(SM_OT + 2048 <= SM_W + 73728, "alias overflow");
constexpr uint32_t SM_MEMB = SM_W + 147456;
constexpr uint32_t SM_MISC = SM_MEMB + 9216;
constexpr uint32_t MB_W = SM_MISC;
constexpr uint32_t MB_WO = SM_MISC + 24;
constexpr uint32_t MB_XT = SM_MISC + 32;
constexpr uint32_t MB_X = SM_MISC + 88;
constexpr uint32_t MB_V = SM_MISC + 56;
constexpr uint32_t MB_ST = SM_MISC + 72;
constexpr uint32_t SM_MX = SM_MISC + 96;
constexpr uint32_t SM_ISC = SM_MISC + 112;
constexpr uint32_t SM_ZERO = SM_MISC + 120;
constexpr uint32_t SM_G = SM_MISC + 124;
constexpr uint32_t SM_RED = SM_MISC + 128;
constexpr uint32_t SM_TP = SM_MISC + 208;
constexpr uint32_t SM_XMAX = SM_MISC + 256;
constexpr uint32_t SM_HINT = SM_OT + 2048;
static_assert(SM_HINT + 192 <= SM_W + 73728, "alias");
constexpr uint32_t SM_TRC = SM_MISC + 512;
constexpr uint32_t K1_SMEM = SM_MISC + 512;
static_assert(SM_PT + 10240 <= SM_MEMB, "alias overflow");
static_assert(K1_SMEM <= 232448, "smem");

enum { BAR_MEM = 1, BAR_QK = 2, BAR_O = 3, BAR_HK = 5, BAR_B = 6, BAR_GO = 7   };
DEVI uint32_t xbuf(int b) { return b == 0 ? SM_WO : SM_XB + (b - 1) * 36864; }
#define EXP_KS 36
#define GOPOS 0
#define GOT 0
#define P1A 30
#define P1B 8
#define APRE 1
#define SSPOS 9
#define HINTS 1
#define RETRY_MODE 0
#define GO_SAFE 0
#define VAPOS 1
#define HFPOS 1
#define ZFENCE 1
#define EF 1
#define XPOS 0
#define POLL_DELAY 2600
#define HINT_DELAY 500
#define R2SLACK 3
#define HW 3

DEVI float absbf2_sum(uint32_t v) { return fabsf(bf_lo(v)) + fabsf(bf_hi(v)); }
DEVI float warp_max_nn(float v) { return __uint_as_float(__reduce_max_sync(0xffffffffu, __float_as_uint(v))); }

DEVI int hint_max(uint2 hv, uint32_t own) {
  const uint32_t o = own << 17;
  const int d0 = (int)((hv.x << 17) - o), d1 = (int)((hv.x << 1) - o), d2 = (int)((hv.y << 17) - o), d3 = (int)((hv.y << 1) - o);
  int d = max(max(d0, d1), max(d2, d3)) >> 17;
  return __reduce_max_sync(0xffffffffu, d);
}

__global__ void __cluster_dims__(3, 1, 1) __launch_bounds__(384, 1)
k_chain(const __grid_constant__ CUtensorMap tm_x, const __grid_constant__ CUtensorMap tm_wq,
        const __grid_constant__ CUtensorMap tm_wk, const __grid_constant__ CUtensorMap tm_wv,
        const __grid_constant__ CUtensorMap tm_wo, const bf16* __restrict__ xg, const bf16* __restrict__ mem0,
        unsigned char* __restrict__ ox, unsigned char* __restrict__ arb) {
  extern __shared__ __align__(1024) unsigned char smem[];
  const uint32_t sb = smem_u32(smem);
  const int tid = threadIdx.x, lane = tid & 31;
  const int wid = __shfl_sync(0xffffffffu, tid >> 5, 0), wg = wid >> 2, w = wid & 3;
  const int rank = blockIdx.x % 3, head = blockIdx.x / 3;
  const float SCL = 0.08838834764831845f * 1.4426950408889634f;

  if (tid == 0) {
    TRG(0);
    for (int i = 0; i < 3; i++) mbar_init(sb + MB_W + 8 * i, 1);
    mbar_init(sb + MB_WO, 1);
    mbar_init(sb + MB_XT, 1); mbar_init(sb + MB_XT + 8, 1); mbar_init(sb + MB_XT + 16, 1);
    mbar_init(sb + MB_X, 1);
    mbar_init(sb + MB_V, 1); mbar_init(sb + MB_V + 8, 1);
    mbar_init(sb + MB_ST, 1); mbar_init(sb + MB_ST + 8, 1);
    asm volatile("fence.mbarrier_init.release.cluster;" ::: "memory");
    fence_async_smem();
    const CUtensorMap* m0 = rank == 2 ? &tm_wv : &tm_wq;
    const CUtensorMap* m1 = rank == 2 ? &tm_wv : &tm_wk;
    const uint64_t pol = policy_evict_first();
    const int c0 = head * DH + (rank == 1 ? 64 : 0), c1 = head * DH + (rank >= 1 ? 64 : 0);
    for (int c = 0; c < 3; c++) {
      mbar_expect(sb + MB_W + 8 * c, 2 * 24576);
      if (EF) {
        tma2d_hint(sb + SM_W + c * 24576, m0, c0, c * 192, sb + MB_W + 8 * c, pol);
        tma2d_hint(sb + SM_W + 73728 + c * 24576, m1, c1, c * 192, sb + MB_W + 8 * c, pol);
      } else {
        tma2d(sb + SM_W + c * 24576, m0, c0, c * 192, sb + MB_W + 8 * c);
        tma2d(sb + SM_W + 73728 + c * 24576, m1, c1, c * 192, sb + MB_W + 8 * c);
      }
    }
    for (int c = 0; c < 3; c++) tma2d_prefetch(&tm_wo, rank * 192 + c * 64, head * DH);
    mbar_expect(sb + MB_XT, 36864); mbar_expect(sb + MB_XT + 8, 36864);
  }
  __syncwarp();
  cluster_arrive();
  {
    if (tid < 32) reinterpret_cast<uint4*>(arb)[blockIdx.x * 32 + tid] = make_uint4(0, 0, 0, 0);
    if (tid < 64 && blockIdx.x == 94) reinterpret_cast<uint4*>(arb + 32 * 24576)[tid] = make_uint4(0, 0, 0, 0);
    if (blockIdx.x == 95) {
      if (tid < 128) g_flags[tid] = 0;
      if (tid == 128) g_epoch = g_epoch + 1;
    }
    float mx = 0.f;
    for (int i = tid; i < 8 * DM; i += 384) {
      int r = i / DM, c = i % DM;
      bf16 v = mem0[i];
      *reinterpret_cast<bf16*>(smem + SM_MEMB + c * 16 + r * 2) = v;
      mx = fmaxf(mx, fabsf(__bfloat162float(v)));
    }
    mx = warp_max_nn(mx);
    float xm = 0.f;
    if (blockIdx.x < NSEG) {
      const uint4* xp = reinterpret_cast<const uint4*>(xg + (size_t)blockIdx.x * SEG * DM);
#pragma unroll
      for (int i = 0; i < 6; i++) {
        uint4 v = __ldg(xp + i * 384 + tid);
        uint32_t a[4] = {v.x, v.y, v.z, v.w};
#pragma unroll
        for (int j = 0; j < 4; j++) xm = fmaxf(xm, fmaxf(fabsf(bf_lo(a[j])), fabsf(bf_hi(a[j]))));
      }
      xm = warp_max_nn(xm);
    }
    float* red = reinterpret_cast<float*>(smem + SM_XMAX);
    if (lane == 0) { red[tid >> 5] = mx; red[16 + (tid >> 5)] = xm; }
    __threadfence();
    __syncthreads();
    if (tid == 0) {
      float a = 0.f, b = 0.f;
      for (int i = 0; i < 12; i++) { a = fmaxf(a, red[i]); b = fmaxf(b, red[16 + i]); }
      float* m4 = reinterpret_cast<float*>(smem + SM_MX);
      m4[0] = m4[1] = m4[2] = m4[3] = a;
      *reinterpret_cast<float*>(smem + SM_ISC) = 1.0f;
      *reinterpret_cast<float*>(smem + SM_ZERO) = 0.0f;
      *reinterpret_cast<uint32_t*>(smem + SM_TP + 8) = 0;
      if (blockIdx.x < NSEG) g_pub[192 + blockIdx.x] = b;
      __threadfence();
    }
    asm volatile("griddepcontrol.launch_dependents;" ::: "memory");
  }
  cluster_wait();
  if (tid == 0) {
    for (int g = 0; g < 2; g++)
      for (int c = 0; c < 3; c++) {
        int kc = rank * 3 + c;
        tma2d_mc(sb + xbuf(2 - g) + kc * 4096, &tm_x, kc * 64, g * SEG, sb + MB_XT + 8 * g, (uint16_t)7);
      }
  }
  const uint32_t dl0 = 0u - ((uint32_t)rank << 24), dl1 = dl0 + (1u << 24), dl2 = dl0 + (2u << 24);
  if (mapa(sb, 0) != sb + dl0 || mapa(sb, 1) != sb + dl1 || mapa(sb, 2) != sb + dl2) __trap();

  auto send_vx = [&](int g, uint32_t dl) {
    bulk_s2c(sb + dl + SM_VX + (g & 1) * 8192, sb + SM_PX + (g & 3) * 8192, 8192, sb + dl + MB_V + 8 * (g & 1));
  };
  if (wg < 2) {
    uint32_t A[36][4];
    const uint32_t wofs = sb + SM_W + wg * 73728 + (((lane >> 4) * 8 + (lane & 7)) * 128 + (((2 * w + ((lane >> 3) & 1)) ^ (lane & 7)) << 4));
    {
#pragma unroll
      for (int ks = KS_SM; ks < 36; ks++) {
        if (ks % 12 == 0 || ks == KS_SM) mbar_wait(sb + MB_W + 8 * (ks / 12), 0);
        ldsm4t(A[ks], wofs + ks * 2048);
      }
      if (rank == 2) {
        float s0 = 0.f, s1 = 0.f;
#pragma unroll
        for (int ks = 0; ks < KS_SM; ks++) ldsm4t(A[ks], wofs + ks * 2048);
#pragma unroll
        for (int ks = 0; ks < 36; ks++) { s0 += absbf2_sum(A[ks][0]) + absbf2_sum(A[ks][2]); s1 += absbf2_sum(A[ks][1]) + absbf2_sum(A[ks][3]); }
        s0 += __shfl_xor_sync(~0u, s0, 1); s0 += __shfl_xor_sync(~0u, s0, 2);
        s1 += __shfl_xor_sync(~0u, s1, 1); s1 += __shfl_xor_sync(~0u, s1, 2);
        s0 = warp_max_nn(fmaxf(s0, s1));
        if (lane == 0) sts32(sb + SM_RED + (tid >> 5) * 4, __float_as_uint(s0));
      }
    }
    if (tid == 0) TRG(1);
    cluster_arrive();
    cluster_wait();

    const uint32_t l16 = opaque(sb + lane * 16);
    int xb = 0, xph = 0;
    auto load_a = [&]() {
#pragma unroll
      for (int ks = 0; ks < KS_SM; ks++) ldsm4t(A[ks], wofs + ks * 2048);
    };
    auto filler_mma = [&](float* acc, uint32_t xo, auto K0, auto K1, auto hook) {
      const uint64_t d0 = mkdesc(sb + xo, 16, 1024);
      WG_FENCE();
#pragma unroll
      for (int i = K0.value; i < K1.value; i++) {
        const int ks = i < SSPOS ? i + KS_SM : i < SSPOS + KS_SM ? i - SSPOS : i;
        const uint64_t db = d0 + (uint64_t)(((ks >> 2) * 4096 + (ks & 3) * 32) >> 4);
        if (ks < KS_SM) wg_n32_ss_ta(acc, mkdesc(sb + SM_W + wg * 73728 + ks * 2048, 16, 1024), db, 1);
        else if (i == 0) wg_n32_rs_z(acc, A[ks], db);
        else wg_n32_rs(acc, A[ks], db, 1);
      }
      WG_COMMIT();
      hook();
      if (APRE) load_a();
      WG_WAIT(0);
    };
    auto nop = []() {};
    auto x_wait = [&]() { mbar_wait(sb + MB_XT + 8 * xb, xph); };
    auto x_next = [&]() { if (++xb == 3) { xb = 0; xph ^= 1; } };
    auto load_x = [&](int g, int b) {
      mbar_expect(sb + MB_XT + 8 * b, 36864);
#pragma unroll
      for (int c = 0; c < 3; c++) {
        const int kc = rank * 3 + c;
        tma2d_mc(sb + xbuf(b) + kc * 4096, &tm_x, kc * 64, g * SEG, sb + MB_XT + 8 * b, (uint16_t)7);
      }
    };
    auto mem_proj = [&](uint32_t& lo, uint32_t& hi) {
      if (!APRE) load_a();
      bar_sync(BAR_MEM, 384);
      float c[3][4];
      uint32_t b[18][4];
      constexpr int PF = 3;
#pragma unroll
      for (int k2 = 0; k2 < PF; k2++) ldsm4t(b[k2], l16 + SM_MEMB + k2 * 512);
#pragma unroll
      for (int k2 = 0; k2 < 18; k2++) {
        const int ka = 2 * k2, kb = 2 * k2 + 1;
        if (ka < 3) mma16z(c[ka], A[ka][0], A[ka][1], A[ka][2], A[ka][3], b[k2][0], b[k2][1]); else mma16(c[ka % 3], A[ka], b[k2][0], b[k2][1]);
        if (kb < 3) mma16z(c[kb], A[kb][0], A[kb][1], A[kb][2], A[kb][3], b[k2][2], b[k2][3]); else mma16(c[kb % 3], A[kb], b[k2][2], b[k2][3]);
        if (k2 == 1) { ldsm4t(b[PF + 1], l16 + SM_MEMB + (PF + 1) * 512); ldsm4t(b[PF + 2], l16 + SM_MEMB + (PF + 2) * 512); }
        else if (k2 == 0) ldsm4t(b[PF], l16 + SM_MEMB + PF * 512);
        else if (k2 + PF + 1 < 18) ldsm4t(b[k2 + PF + 1], l16 + SM_MEMB + (k2 + PF + 1) * 512);
      }
      const float isc = __uint_as_float(lds32(sb + SM_ISC));
      lo = pack_bf16((c[0][0] + c[1][0] + c[2][0]) * isc, (c[0][1] + c[1][1] + c[2][1]) * isc);
      hi = pack_bf16((c[0][2] + c[1][2] + c[2][2]) * isc, (c[0][3] + c[1][3] + c[2][3]) * isc);
    };
    auto hint_fetch = [&](int s) {
      if (and_v(l16, 496u) < 192u) cp16(l16 + SM_HINT, arb + 32 * 24576 + s * 256 + and_v(l16, 496u));
    };
    auto hint_read = [&](int s) {
      const uint32_t ho = min(and_v(l16, 496u), 368u) >> 1;
      int dm, lim = 0;
      cp_wait_all();
      __syncwarp();
      uint2 hv = lds64(sb + SM_HINT + ho);
      while (__any_sync(0xffffffffu, (hv.x & hv.y & 0x80008000u) != 0x80008000u) && !spin_fail(++lim, SPIN_LIMIT, 300 + s))
        hv = ld_relaxed_v2(arb + 32 * 24576 + s * 256 + ho);
      const uint2 own = lds64v(sb + SM_TP);
      dm = hint_max(hv, own.x);
      TRV(3, dm + 100); TR(7);
      sts64(sb + SM_TP + 8, s + 1, own.y + POLL_DELAY + min(dm, 1000) * 58 * HINTS);
    };
    if (tid == 0) {
      mbar_expect(sb + MB_X, rank < 2 ? 1280 + 2048 : 2560);
      if (rank < 2) { mbar_expect(sb + MB_V, 8192); mbar_expect(sb + MB_V + 8, 8192); }
    }
    __syncwarp();

    if (rank < 2) {
      auto epilogue = [&](const float* acc, int g) {
        const uint32_t dst = sb + SM_PX + (g & 3) * 8192 +
                             (wg ? 4096 + ((lane >> 3) & 1) * 1024 + (2 * w + (lane >> 4)) * 128 + (lane & 7) * 16 : w * 512 + lane * 16);
        stsm4(dst, pack_bf16(acc[0], acc[1]), pack_bf16(acc[4], acc[5]), pack_bf16(acc[2], acc[3]), pack_bf16(acc[6], acc[7]));
        stsm4(dst + 2048, pack_bf16(acc[8], acc[9]), pack_bf16(acc[12], acc[13]), pack_bf16(acc[10], acc[11]), pack_bf16(acc[14], acc[15]));
      };
      { float acc[16]; x_wait(); filler_mma(acc, xbuf(2), IC<0>{}, IC<36>{}, nop); x_next(); epilogue(acc, 0); }
      cluster_arrive();
      { float acc[16]; x_wait(); filler_mma(acc, xbuf(1), IC<0>{}, IC<36>{}, nop); x_next(); epilogue(acc, 1); }
      cluster_wait();
      if (tid == 224) load_x(2, 2);
      __syncwarp();
      if (tid == 0) TRG(2);
      const uint32_t dO = rank ? dl0 : dl1;
#pragma unroll 1
      for (int s = 0; s <= NSEG; s++) {
        const uint32_t pxo = SM_PX + (s & 3) * 8192;
        if (s < NSEG) {
        uint32_t lo, hi;
        mem_proj(lo, hi);
        TR(2);
        stsm2(l16 + and_v(l16, wg ? 0u : 128u) + SM_QM + (wg ? 1024 + w * 256 : (w >> 1) * 512 + (w & 1) * 128), lo, hi);
        if (wid < 5) {
          bar_sync(BAR_QK, 256);
          uint32_t q[8], k[8];
          const uint32_t ka = l16 + (wg ? SM_QM + 1024 : pxo + 4096 + w * 1024);
          ldsm4t(q, l16 + SM_QM); ldsm4t(k, ka);
          ldsm4t(q + 4, l16 + SM_QM + 512); ldsm4t(k + 4, ka + 512);
          const uint32_t a2 = half_v(l16 + sb) + SM_SB + (wg ? 0 : (w + 1)) * 256 + rank * 1280, mb = sb + MB_X;
          float s0[4], s1[4], s2[4], s3[4];
          mma16z(s0, q[0], q[1], q[2], q[3], k[0], k[1]);
          mma16z(s1, q[0], q[1], q[2], q[3], k[2], k[3]);
          mma16z(s2, q[4], q[5], q[6], q[7], k[4], k[5]);
          mma16z(s3, q[4], q[5], q[6], q[7], k[6], k[7]);
          const float x = ((s0[0] + s1[2]) + (s2[0] + s3[2])) * SCL, y = ((s0[1] + s1[3]) + (s2[1] + s3[3])) * SCL;
          sts64f(a2, x, y); st_async64f(a2 + dl2, x, y, mb + dl2); st_async64f(a2 + dO, x, y, mb + dO);
          bar_arrive(BAR_B, s + 1 < NSEG ? 384 : 256);
        } else {
          bar_arrive(BAR_QK, 256);
          bar_sync(BAR_B, s + 1 < NSEG ? 384 : 256);
        }
        }
        TR(4);
        if (HFPOS == 0 && wid == 2) hint_fetch(s);
        if (wid == 5 || wid == 6) {
          if (s > 0) {
            const int g = s - 1, hf = wid - 5;
            mbar_wait(sb + MB_ST + 8 * (g & 1), (g >> 1) & 1);
            if (s == NSEG) bar_sync(BAR_QK, 96);
            const uint32_t st = half_v(l16 + sb) + (g & 1) * 4096 + rank * 1536 + hf * 256;
            const int ln = and_v(l16, 496u) >> 4;
            const int r0 = 16 * rank + 8 * hf + (ln >> 2) - 2 * (ln & 3);
            float p[5][2];
#pragma unroll
            for (int j = 0; j < 5; j++) {
              const float2 a = lds64f(st + SM_ST0 + j * 512), b = lds64f(st + SM_ST1 + j * 512);
              p[j][0] = a.x + b.x; p[j][1] = a.y + b.y;
              if (j > 0) {
                p[j][0] = 8 * (j - 1) > r0 ? -INFINITY : p[j][0];
                p[j][1] = 8 * (j - 1) + 1 > r0 ? -INFINITY : p[j][1];
              }
            }
            float m = fmaxf(fmaxf(fmaxf(p[0][0], p[0][1]), fmaxf(p[1][0], p[1][1])), fmaxf(fmaxf(p[2][0], p[2][1]), fmaxf(p[3][0], p[3][1])));
            m = fmaxf(m, fmaxf(p[4][0], p[4][1]));
            m = fmaxf(m, __shfl_xor_sync(~0u, m, 1));
            m = fmaxf(m, __shfl_xor_sync(~0u, m, 2));
#pragma unroll
            for (int j = 0; j < 5; j++) { p[j][0] = ex2(p[j][0] - m); p[j][1] = ex2(p[j][1] - m); }
            float l = (((p[0][0] + p[0][1]) + (p[1][0] + p[1][1])) + ((p[2][0] + p[2][1]) + (p[3][0] + p[3][1]))) + (p[4][0] + p[4][1]);
            l += __shfl_xor_sync(~0u, l, 1);
            l += __shfl_xor_sync(~0u, l, 2);
            l = rcp_fast(l);
            const uint32_t pt = sb + dl2 + SM_PT + (g & 3) * 2560 + rank * 1280 + hf * 128 + ln * 4;
#pragma unroll
            for (int j = 0; j < 5; j++) st_async32(pt + j * 256, pack_bf16(p[j][0] * l, p[j][1] * l), sb + dl2 + MB_ST + 8 * (g & 1));
            TR(15);
          }
        } else if (s < NSEG) {
          const int p0 = wid == 7 ? 6 : wid, mt = p0 >= 3;
          const uint32_t qa = l16 + pxo + mt * 2048;
          uint32_t a[4][4];
          ldsm4t(a[0], qa); ldsm4t(a[1], qa + 512); ldsm4t(a[2], qa + 1024); ldsm4t(a[3], qa + 1536);
#pragma unroll 1
          for (int p = p0; p <= p0 + (wid >= 4); p++) {
            const int j = p - 3 * mt;
            const uint32_t ka = l16 + (j ? pxo + 4096 + (j - 1) * 1024 : SM_QM + 1024);
            uint32_t k[8];
            ldsm4t(k, ka); ldsm4t(k + 4, ka + 512);
            float d[4], e[4];
            mma16z(d, a[0][0], a[0][1], a[0][2], a[0][3], k[0], k[1]);
            mma16z(e, a[1][0], a[1][1], a[1][2], a[1][3], k[2], k[3]);
            mma16(d, a[2], k[4], k[5]);
            mma16(e, a[3], k[6], k[7]);
            const uint32_t sta = half_v(l16 + sb) + SM_ST0 + (s & 1) * 4096 + p * 512;
            sts64f(sta, (d[0] + e[0]) * SCL, (d[1] + e[1]) * SCL); sts64f(sta + 256, (d[2] + e[2]) * SCL, (d[3] + e[3]) * SCL);
          }
          fence_async_smem();
          TR(6);
          if (wid == 0) {
            bar_sync(BAR_HK, 192);
            if (s == NSEG - 1) bar_arrive(BAR_QK, 96);
            mbar_wait(sb + MB_X, s & 1);
            if (s == 0) mbar_wait(sb + MB_V, 0);
            if (lane == 0) {
              const uint32_t off = (s & 1) * 4096 + (rank ? 0 : 1536);
              bulk_s2c(sb + dO + SM_ST1 + off, sb + SM_ST0 + off, rank ? 1536 : 2560, sb + dO + MB_ST + 8 * (s & 1));
              mbar_expect(sb + MB_ST + 8 * (s & 1), rank ? 2560 : 1536);
              if (s + 3 < NSEG) mbar_expect(sb + MB_V + 8 * (s & 1), 8192);
              if (s + 1 < NSEG) mbar_expect(sb + MB_X, 1280 + 2048);
            }
            __syncwarp();
          } else {
            bar_arrive(BAR_HK, 192);
            if (wid == 2 && s + 1 < NSEG && s > 0) { if (HFPOS == 1) hint_fetch(s); hint_read(s); }
            if (wid == 3 && s + 4 < NSEG) {
              const int g = s + 4, v = (head * 2 + rank) * 12 + lane;
              if (lane < 12) *reinterpret_cast<uint4*>(arb + (g >> 1) * 24576 + (g & 1) * 128 + (v >> 3) * 256 + (v & 7) * 16) = make_uint4(0, 0, 0, 0);
              if (lane == 12) *reinterpret_cast<uint32_t*>(arb + 32 * 24576 + g * 256 + (head * 2 + rank) * 4) = 0;
              if (ZFENCE) __threadfence();
              __syncwarp();
            }
            if (wid == 1 && s + 3 < NSEG) { if (XPOS == 1) mbar_wait(sb + MB_X, s & 1); if (lane == 0) load_x(s + 3, xb == 2 ? 0 : xb + 1); __syncwarp(); }
          }
        }
        if (s + 2 < NSEG) {
          float acc[16];
          x_wait();
          bar_sync(BAR_GO + wg, 256);
          filler_mma(acc, xbuf(xb), IC<0>{}, IC<EXP_KS>{}, nop);
          x_next();
          epilogue(acc, s + 2);
        } else if (APRE) load_a();
        TR(8);
      }
    } else {
      auto epilogue = [&](const float* acc, int g) {
        const uint32_t dst = l16 + SM_PX + (g & 3) * 8192 + wid * 1024;
        stsm4(dst, pack_bf16(acc[0], acc[1]), pack_bf16(acc[2], acc[3]), pack_bf16(acc[4], acc[5]), pack_bf16(acc[6], acc[7]));
        stsm4(dst + 512, pack_bf16(acc[8], acc[9]), pack_bf16(acc[10], acc[11]), pack_bf16(acc[12], acc[13]), pack_bf16(acc[14], acc[15]));
        fence_async_smem();
      };
      { float acc[16]; x_wait(); filler_mma(acc, xbuf(2), IC<0>{}, IC<36>{}, nop); x_next(); epilogue(acc, 0); }
      cluster_arrive();
      bar_sync(BAR_QK, 256);
      if (tid == 0) { send_vx(0, dl0); send_vx(0, dl1); }
      __syncwarp();
      { float acc[16]; x_wait(); filler_mma(acc, xbuf(1), IC<0>{}, IC<36>{}, nop); x_next(); epilogue(acc, 1); }
      bar_sync(BAR_QK, 256);
      if (tid == 0) send_vx(1, dl1);
      __syncwarp();
      cluster_wait();
      if (tid == 224) load_x(2, 2);
      __syncwarp();
      if (tid == 0) TRG(2);
      unsigned char* oxp = ox + (size_t)head * 8192;
#pragma unroll 1
      for (int s = 0; s <= NSEG + 1; s++) {
        if (s < NSEG) {
          uint32_t lo, hi;
          mem_proj(lo, hi);
          TR(2);
          const uint32_t a = half_v(l16 + sb) + SM_VM + ((s + 2) & 3) * 2048 + wid * 256, mb = sb + MB_X;
          sts64(a, lo, hi); st_async64(a + dl0, lo, hi, mb + dl0); st_async64(a + dl1, lo, hi, mb + dl1);
          if (s + 1 < NSEG) bar_arrive(BAR_B, 384);
          if (wid == 2) hint_fetch(s);
          TR(4);
        }
        if (s > 1) {
          const int g = s - 2, mt = wid & 1, eq = wid >> 1;
          uint32_t pm[2], p0[4], p1[4];
          const uint32_t pt = l16 + SM_PT + (g & 3) * 2560 + mt * 1280;
          mbar_wait(sb + MB_ST + 8 * (g & 1), (g >> 1) & 1);
          ldsm2(pm, pt); ldsm4(p0, pt + 256); ldsm4(p1, pt + 768);
          const uint32_t vma = half_v(l16 + sb) + SM_VM + ((g + 2) & 3) * 2048 + eq * 512;
          const uint2 bm0 = lds64(vma), bm1 = lds64(vma + 256);
          const uint32_t vx = l16 + and_v(l16, 384u) + SM_PX + (g & 3) * 8192 + eq * 2048;
          const int ln = and_v(l16, 496u) >> 4;
          const int row = 16 * mt + (ln & 15);
          const uint32_t os = sb + SM_OS + (g & 1) * 8192 + (eq >> 1) * 4096 + row * 128;
#pragma unroll
          for (int o2 = 0; o2 < 2; o2++) {
            float d[2][4];
            uint32_t bx[2][4];
            ldsm4(bx[0], vx + o2 * 1024); ldsm4(bx[1], vx + o2 * 1024 + 128);
            mma8z(d[0], pm[0], pm[1], o2 ? bm1.x : bm0.x);
            mma8z(d[1], pm[0], pm[1], o2 ? bm1.y : bm0.y);
            mma16(d[0], p0, bx[0][0], bx[0][1]); mma16(d[1], p0, bx[1][0], bx[1][1]);
            mma16(d[0], p1, bx[0][2], bx[0][3]); mma16(d[1], p1, bx[1][2], bx[1][3]);
            const int ch = (eq & 1) * 4 + o2 * 2 + (ln >> 4);
            stsm4(os + ((ch ^ (ln & 7)) << 4), pack_bf16(d[0][0], d[0][1]), pack_bf16(d[0][2], d[0][3]),
                  pack_bf16(d[1][0], d[1][1]), pack_bf16(d[1][2], d[1][3]));
          }
          fence_async_smem();
        }
        TR(6);
        auto ship = [&]() {
          if (tid == 32 && s >= 2) { bulk_s2g(oxp + (size_t)(s - 2) * (NH * 8192), sb + SM_OS + (s & 1) * 8192, 8192); bulk_commit(); }
          __syncwarp();
        };
        if (wid == 1) {
          if (lane == 0 && s >= 3) { bulk_wait0(); fence_async_global(); red_relaxed_add(&g_flags[s - 3], 1u); }
          __syncwarp();
          bar_sync(BAR_QK, 256);
        } else {
          if (s + 2 < NSEG) bar_arrive(BAR_QK, 256); else bar_sync(BAR_QK, 256);
          if (wid == 0 && s < NSEG) {
            mbar_wait(sb + MB_X, s & 1);
            if (lane == 0) {
              if (s + 2 < NSEG) send_vx(s + 1, dl0);
              mbar_expect(sb + MB_ST + 8 * (s & 1), 2560);
              if (s + 1 < NSEG) mbar_expect(sb + MB_X, 2560);
            }
            __syncwarp();
          }
          if (wid == 7 && s + 3 < NSEG) { if (XPOS == 1) mbar_wait(sb + MB_X, s & 1); if (lane == 0) load_x(s + 3, xb == 2 ? 0 : xb + 1); __syncwarp(); }
          if (wid == 2 && s + 1 < NSEG && s > 0) hint_read(s);
        }
        if (s + 2 < NSEG) {
          float acc[16];
          x_wait();
          bar_sync(BAR_GO + wg, 256);
          filler_mma(acc, xbuf(xb), IC<0>{}, IC<EXP_KS>{}, ship);
          x_next();
          epilogue(acc, s + 2);
          if (s + 3 < NSEG) bar_arrive(BAR_HK, 288);
        } else {
          ship();
          if (APRE) load_a();
        }
        TR(8);
      }
      if (tid == 32) { bulk_wait0(); fence_async_global(); red_relaxed_add(&g_flags[NSEG - 1], 1u); TRG(7); }
      __syncwarp();
    }
    TRDUMP();
    cluster_arrive();
    cluster_wait();
  } else {
    const int t = tid - 256;
    cluster_arrive();
    cluster_wait();
    if (t == 0) {
      mbar_expect(sb + MB_WO, 49152);
      for (int c = 0; c < 3; c++) tma2d(sb + SM_WO + c * 16384, &tm_wo, rank * 192 + c * 64, head * DH, sb + MB_WO);
    }
    bar_arrive(BAR_MEM, 384);
    const uint32_t l16 = opaque(sb + lane * 16);
    const uint32_t vxo = (rank == 2 ? SM_PX : SM_VX) + w * 2048;
    const int vxm = rank == 2 ? 3 : 1;
    uint32_t va[2][2][4];
    auto load_va = [&](int g) {
      if (rank < 2 && g + 1 < NSEG) mbar_wait(sb + MB_V + 8 * (g & 1), (g >> 1) & 1);
      const uint32_t a = l16 + vxo + (g & vxm) * 8192;
      ldsm4(va[0][0], a); ldsm4(va[0][1], a + 512); ldsm4(va[1][0], a + 1024); ldsm4(va[1][1], a + 1536);
    };
    uint32_t WO[3][8][4];
    {
      mbar_wait(sb + MB_WO, 0);
      const int mat = lane >> 3, r = lane & 7;
      float mx = 0.f;
#pragma unroll
      for (int tt = 0; tt < 3; tt++) {
        const int idx = 6 * w + 2 * tt + (mat & 1);
        const uint32_t base = sb + SM_WO + (idx >> 3) * 16384 + ((mat >> 1) * 8 + r) * 128 + (((idx & 7) ^ r) << 4);
        float s0 = 0.f, s1 = 0.f;
#pragma unroll
        for (int ks = 0; ks < 8; ks++) {
          ldsm4t(WO[tt][ks], base + ks * 2048);
          s0 += absbf2_sum(WO[tt][ks][0]) + absbf2_sum(WO[tt][ks][2]);
          s1 += absbf2_sum(WO[tt][ks][1]) + absbf2_sum(WO[tt][ks][3]);
        }
        s0 += __shfl_xor_sync(~0u, s0, 1); s0 += __shfl_xor_sync(~0u, s0, 2);
        s1 += __shfl_xor_sync(~0u, s1, 1); s1 += __shfl_xor_sync(~0u, s1, 2);
        mx = fmaxf(mx, fmaxf(s0, s1));
      }
      cluster_arrive();
      mx = warp_max_nn(mx);
      if (lane == 0) sts32(sb + SM_RED + (8 + w) * 4, __float_as_uint(mx));
      cluster_wait();
      load_va(0);
      bar_sync(BAR_O, 128);
      if (t == 0) {
        const float* red = reinterpret_cast<const float*>(smem + SM_RED);
        float a = 0.f, b = 0.f;
        if (rank == 2) for (int i = 0; i < 8; i++) a = fmaxf(a, red[i]);
        for (int i = 8; i < 12; i++) b = fmaxf(b, red[i]);
        g_pub[blockIdx.x] = a; g_pub[96 + blockIdx.x] = b;
        __threadfence();
        const uint32_t old = atomicAdd(&g_cnt, 1u);
        const uint32_t target = (old / K1_CTAS + 1) * K1_CTAS;
        int lim = 0;
        while ((int)(ld_acquire(&g_cnt) - target) < 0 && !spin_fail(++lim, SPIN_LIMIT, 1)) {}
      }
      bar_sync(BAR_O, 128);
      const uint32_t* pub = reinterpret_cast<const uint32_t*>(g_pub);
      float w1 = __uint_as_float(ld_relaxed(pub + lane * 3 + 2));
      float w2 = fmaxf(fmaxf(__uint_as_float(ld_relaxed(pub + 96 + lane * 3)), __uint_as_float(ld_relaxed(pub + 96 + lane * 3 + 1))),
                       __uint_as_float(ld_relaxed(pub + 96 + lane * 3 + 2)));
      const float xm = t < NSEG ? __uint_as_float(ld_relaxed(pub + 192 + t)) : 0.f;
      w1 = warp_max_nn(w1);
#pragma unroll
      for (int o = 16; o; o >>= 1) w2 += __shfl_xor_sync(~0u, w2, o);
      const float G = w1 * w2 * 1.1f;
      if (t < NSEG) sts32(sb + SM_XMAX + t * 4, __float_as_uint(xm * G));
      sts32(sb + SM_G, __float_as_uint(G));
      sts32(sb + SM_MX + w * 4, __float_as_uint(__uint_as_float(lds32(sb + SM_MX + w * 4)) * G));
    }
    if (t == 0) TRG(3);
    const uint32_t l8 = opaque(sb + lane * 8);
    auto hint_write = [&](int s) {
      uint32_t g;
      asm volatile("st.volatile.shared.b32 [%0], %1;" ::"r"(sb + SM_TP + 16), "r"(s) : "memory");
      asm volatile("mov.u32 %0, %%globaltimer_lo;" : "=r"(g)::"memory");
      const uint32_t c = clk32();
      g >>= 5;
      sts64(sb + SM_TP, g, c);
      asm volatile("st.relaxed.gpu.global.u16 [%0], %1;" ::"l"(arb + 32 * 24576 + s * 256 + blockIdx.x * 2),
                   "h"((unsigned short)((g - (rank == 2 ? R2SLACK : 0)) | 0x8000u)) : "memory");
    };
    if (w == HW) sts64(sb + SM_TP + 8, 1, clk32() + POLL_DELAY - 800);
#pragma unroll 1
    for (int sv_ = 0; sv_ < NSEG - 1; sv_++) {
      const int s = __shfl_sync(0xffffffffu, sv_, 0);
      TR(9);
      unsigned char* arw = arb + (uint32_t)((s >> 1) * 24576 + (s & 1) * 128 + (rank * 8 + w * 2) * 1024 - sb + l16 + and_v(l16, 384u));
      bar_sync(BAR_B, 384);
      const float4 mx4 = lds128f(sb + SM_MX);
      const uint32_t zero = lds32(sb + SM_ZERO);
      const float bound = fmaxf(fmaxf(fmaxf(mx4.x, mx4.y), fmaxf(mx4.z, mx4.w)), __uint_as_float(lds32(sb + SM_XMAX + s * 4)));
      int e = (int)(__float_as_uint(bound) >> 23);
      e = min(max(e, 30), 230);
      sts64(sb + SM_ISC, (uint32_t)(e - 14) << 23, (uint32_t)(127 + 14 + 127 - e) << 23);
      const uint32_t vma = l8 + SM_VM + ((s + 2) & 3) * 2048 + w * 512;
      mbar_wait_fast(sb + MB_X, s & 1);
      TR(11);
      float sv[10];
      uint2 vm0, vm1;
      {
        float2 a[5], b[5];
#pragma unroll
        for (int j = 0; j < 5; j++) { a[j] = lds64f(l8 + SM_SB + j * 256); b[j] = lds64f(l8 + SM_SB + 1280 + j * 256); }
        vm0 = lds64(vma); vm1 = lds64(vma + 256);
#pragma unroll
        for (int j = 0; j < 5; j++) { sv[2 * j] = a[j].x + b[j].x; sv[2 * j + 1] = a[j].y + b[j].y; }
      }
      float m = fmaxf(fmaxf(fmaxf(sv[0], sv[1]), fmaxf(sv[2], sv[3])), fmaxf(fmaxf(sv[4], sv[5]), fmaxf(sv[6], sv[7])));
      m = fmaxf(m, fmaxf(sv[8], sv[9]));
      m = fmaxf(m, __shfl_xor_sync(~0u, m, 1));
      m = fmaxf(m, __shfl_xor_sync(~0u, m, 2));
      uint32_t pb[5];
#pragma unroll
      for (int j = 0; j < 5; j++) pb[j] = pack_bf16(ex2(sv[2 * j] - m), ex2(sv[2 * j + 1] - m));
      TR(12);
      float o0[4], o1[4], ls[4];
      const uint32_t ONE = 0x3f803f80u;
      mma8z(o0, vm0.x, vm0.y, pb[0]);
      mma8z(o1, vm1.x, vm1.y, pb[0]);
      mma8z(ls, ONE, ONE, pb[0]);
      mma16(o0, va[0][0], pb[1], pb[2]);
      mma16(o1, va[1][0], pb[1], pb[2]);
      mma16r(ls, ONE, ONE, ONE, ONE, pb[1], pb[2]);
      mma16(o0, va[0][1], pb[3], pb[4]);
      mma16(o1, va[1][1], pb[3], pb[4]);
      mma16r(ls, ONE, ONE, ONE, ONE, pb[3], pb[4]);
      stsm4(l16 + SM_OT + w * 512, pack_bf16(o0[0], o0[1]), pack_bf16(o0[2], o0[3]), pack_bf16(o1[0], o1[1]), pack_bf16(o1[2], o1[3]));
      bar_sync(BAR_O, 128 + (__float_as_uint(ls[2]) & zero));
      TR(13);
      float d[2][3][4];
      uint32_t b[4][4];
#pragma unroll
      for (int k2 = 0; k2 < 4; k2++) ldsm4t(b[k2], l16 + SM_OT + k2 * 512);
      const float r0 = rcp_fast(ls[0]), r1 = rcp_fast(ls[1]);
#pragma unroll
      for (int k2 = 0; k2 < 4; k2++) {
#pragma unroll
        for (int hh = 0; hh < 2; hh++)
#pragma unroll
          for (int tt = 0; tt < 3; tt++) {
            const uint32_t* a0 = WO[tt][2 * k2 + hh];
            if (k2 == 0) mma16z(d[hh][tt], a0[0], a0[1], a0[2], a0[3], b[k2][2 * hh], b[k2][2 * hh + 1]);
            else mma16(d[hh][tt], a0, b[k2][2 * hh], b[k2][2 * hh + 1]);
          }
      }
      const int cnt = 256 + (!GO_SAFE ? 0 : (__float_as_uint(d[0][0][0]) | __float_as_uint(d[0][1][0]) | __float_as_uint(d[0][2][0]) |
                                             __float_as_uint(d[1][0][0]) | __float_as_uint(d[1][1][0]) | __float_as_uint(d[1][2][0])) & zero);
      if (s + 2 < NSEG) { bar_arrive(BAR_GO, cnt); bar_arrive(BAR_GO + 1, cnt); }
      const float sc2 = __uint_as_float(lds32(sb + SM_ISC + 4));
      uint2 tp = lds64v(sb + SM_TP + 8);
      const float f0 = sc2 * r0, f1 = sc2 * r1;
      uint32_t h[6];
#pragma unroll
      for (int tt = 0; tt < 3; tt++) {
        h[2 * tt] = pack_f16(fmaf(d[1][tt][0], f0, d[0][tt][0] * f0), fmaf(d[1][tt][1], f1, d[0][tt][1] * f1));
        h[2 * tt + 1] = pack_f16(fmaf(d[1][tt][2], f0, d[0][tt][2] * f0), fmaf(d[1][tt][3], f1, d[0][tt][3] * f1));
      }
      red_f16x8(arw, h[0], h[1], h[2], 0x3c00u);
      red_f16x8(arw + 1024, h[3], h[4], h[5], 0x3c00u);
      TR(14);
      if (VAPOS == 0) load_va(s + 1);
      const unsigned char* ar = arw + (w * 6 - rank * 8 - w * 2) * 1024;
      {
        int lim = 0;
        while (tp.x != (uint32_t)s + 1 && !spin_fail(++lim, SPIN_LIMIT * 16, 300 + s)) tp = lds64v(sb + SM_TP + 8);
        while ((int)(clk32() - tp.y) < 0) {}
      }
      TR(6);
      uint32_t q[18];
      int lim = 0;
      uint4 v[6];
#pragma unroll
      for (int i = 0; i < 6; i++) v[i] = ld_relaxed_v4(ar + i * 1024);
      if (VAPOS == 1) load_va(s + 1);
      while (true) {
        uint32_t bad = 0;
#pragma unroll
        for (int i = 0; i < 6; i++) { bad |= v[i].w ^ 0x5000u; q[3 * i] = h2b(v[i].x); q[3 * i + 1] = h2b(v[i].y); q[3 * i + 2] = h2b(v[i].z); }
        const uint32_t mb = l16 + SM_MEMB + w * 2304;
#pragma unroll
        for (int i = 0; i < 4; i++) stsm4(mb + i * 512, q[4 * i], q[4 * i + 1], q[4 * i + 2], q[4 * i + 3]);
        stsm2(mb + 2048, q[16], q[17]);
        if (!__any_sync(0xffffffffu, bad != 0) || spin_fail(++lim, SPIN_LIMIT, 100 + s)) break;
#pragma unroll
        for (int i = 0; i < 6; i++) v[i] = ld_relaxed_v4(ar + i * 1024);
      }
      if (w == HW) { bar_sync(BAR_MEM, 384); hint_write(s + 1); } else bar_arrive(BAR_MEM, 384);
      TR(8);
      TRP(0); TRV(3, lim);
      if (rank == 2 && w == 0 && s + 3 < NSEG) {
        bar_sync(BAR_HK, 288);
        if (lane == 0) send_vx(s + 2, dl1);
        __syncwarp();
      }
      uint32_t mx = lds32(sb + SM_ZERO);
#pragma unroll
      for (int i = 0; i < 18; i++) mx = babsmax2(mx, q[i]);
      mx = __reduce_max_sync(0xffffffffu, max(mx << 16, mx & 0xffff0000u));
      sts32(sb + SM_MX + w * 4, __float_as_uint(__uint_as_float(mx) * __uint_as_float(lds32(sb + SM_ISC)) * __uint_as_float(lds32(sb + SM_G))));
      if (t == 0 && s == 0) TRG(4);
      if (t == 0 && s == 62) TRG(5);
    }
    TRDUMP();
    if (t == 0) TRG(6);
    cluster_arrive();
    cluster_wait();
  }
}
constexpr int K2_CTAS = 36;
#define PFO 1
#define PACE0 100
#define PACE1 250
#define PACE_SW 14
__device__ __align__(1024) unsigned char g_h[32 * 18 * 8192];
__device__ __align__(16) uint4 g_E[32 * DM];

#define TR2(i)
constexpr uint32_t S2_A = 0;
constexpr uint32_t S2_RING = 147456;
constexpr uint32_t S2_STG = S2_A + 9 * 8192;
constexpr uint32_t S2_MISC = S2_RING + 73728;
constexpr uint32_t MB2_FULL = S2_MISC, MB2_EMPTY = S2_MISC + 80, MB2_A = S2_MISC + 160, MB2_STG = S2_MISC + 168;
constexpr uint32_t K2_SMEM = S2_MISC + 256;
static_assert(K2_SMEM <= 232448, "smem2");

template <int TB>
DEVI void wg_n64_ss(float* d, uint64_t da, uint64_t db, int sc) {
  asm volatile("{.reg .pred p; setp.ne.b32 p, %34, 0;\n"
               "wgmma.mma_async.sync.aligned.m64n64k16.f32.bf16.bf16 {%0,%1,%2,%3,%4,%5,%6,%7,%8,%9,%10,%11,%12,%13,%14,%15,"
               "%16,%17,%18,%19,%20,%21,%22,%23,%24,%25,%26,%27,%28,%29,%30,%31}, %32, %33, p, 1, 1, 0, %35;}\n"
               : "+f"(d[0]), "+f"(d[1]), "+f"(d[2]), "+f"(d[3]), "+f"(d[4]), "+f"(d[5]), "+f"(d[6]), "+f"(d[7]),
                 "+f"(d[8]), "+f"(d[9]), "+f"(d[10]), "+f"(d[11]), "+f"(d[12]), "+f"(d[13]), "+f"(d[14]), "+f"(d[15]),
                 "+f"(d[16]), "+f"(d[17]), "+f"(d[18]), "+f"(d[19]), "+f"(d[20]), "+f"(d[21]), "+f"(d[22]), "+f"(d[23]),
                 "+f"(d[24]), "+f"(d[25]), "+f"(d[26]), "+f"(d[27]), "+f"(d[28]), "+f"(d[29]), "+f"(d[30]), "+f"(d[31])
               : "l"(da), "l"(db), "r"(sc), "n"(TB));
}
DEVI float2 cmul(float2 a, float2 b) { return make_float2(a.x * b.x - a.y * b.y, a.x * b.y + a.y * b.x); }
DEVI float2 cfma(float2 a, float2 b, float2 c) { return make_float2(fmaf(a.x, b.x, fmaf(-a.y, b.y, c.x)), fmaf(a.x, b.y, fmaf(a.y, b.x, c.y))); }
DEVI void wait_flag(const uint32_t* f, uint32_t target) {
  int lim = 0;
  while (ld_acquire(f) < target && !spin_fail(++lim, SPIN_LIMIT, 1000 + (uint32_t)(f - g_flags))) { __nanosleep(100); }
}

template <int MODE, int NKC, int NST>
DEVI void k2_mainloop(float* acc, uint32_t sb, uint32_t ph0, bool leader, int wg, bool first, bool last) {
  if (!first) bar_sync(4 + wg, 256);
  const uint64_t ds0 = mkdesc(sb + S2_RING, 16, 1024), dw0 = mkdesc(sb + S2_A, 16, 1024);
#pragma unroll
  for (int kc = 0; kc < NKC; kc++) {
    const int st = kc % NST;
    mbar_wait(sb + MB2_FULL + 8 * st, ph0 ^ (kc / NST));
    if (kc == NKC - 1 && !last) bar_arrive(5 - wg, 256);
    const uint64_t ds = ds0 + st * 512, dw = dw0 + kc * 512;
    WG_FENCE();
#pragma unroll
    for (int k = 0; k < 4; k++) {
      if (MODE == 0) wg_n64_ss<0>(acc, dw + 2 * k, ds + 2 * k, (kc | k) != 0);
      if (MODE == 1) wg_n64_ss<0>(acc, ds + 2 * k, dw + 2 * k, (kc | k) != 0);
      if (MODE == 2) wg_n64_ss<1>(acc, ds + 2 * k, dw + 128 * k, (kc | k) != 0);
    }
    WG_COMMIT();
    if (kc > 0) { WG_WAIT(1); if (leader) mbar_arrive(sb + MB2_EMPTY + 8 * ((kc - 1) % NST)); }
  }
  WG_WAIT(0);
  if (leader) mbar_arrive(sb + MB2_EMPTY + 8 * ((NKC - 1) % NST));
}

__global__ void __launch_bounds__(448, 1)
k_side(const __grid_constant__ CUtensorMap tm_xa, const __grid_constant__ CUtensorMap tm_wo,
       const bf16* __restrict__ xa, const bf16* __restrict__ lam_re, const bf16* __restrict__ lam_im,
       const bf16* __restrict__ b_re, const bf16* __restrict__ b_im, const bf16* __restrict__ c_re,
       const bf16* __restrict__ c_im, const bf16* __restrict__ log_dt, const bf16* __restrict__ dskip,
       float* __restrict__ out, const unsigned char* __restrict__ ox, unsigned char* __restrict__ hbuf) {
  extern __shared__ __align__(1024) unsigned char smem[];
  const uint32_t sb = smem_u32(smem);
  const int tid = threadIdx.x, lane = tid & 31;
  const int wid = __shfl_sync(0xffffffffu, tid >> 5, 0), wg = wid >> 2, w = wid & 3;
  const int cta = blockIdx.x;
  const int ct = cta >> 1, par = cta & 1;
  const int dt = cta >> 2, tq = cta & 3;
  if (tid == 0) {
    for (int i = 0; i < 9; i++) { mbar_init(sb + MB2_FULL + 8 * i, 1); mbar_init(sb + MB2_EMPTY + 8 * i, 4); }
    mbar_init(sb + MB2_A, 1); mbar_init(sb + MB2_STG, 1); mbar_init(sb + MB2_STG + 8, 1);
    fence_async_smem();
  }
  __syncthreads();

  if (wg == 2) {
    auto acquire = [&](int st, uint32_t ph) {
      mbar_wait(sb + MB2_EMPTY + 8 * st, ph ^ 1);
      mbar_expect(sb + MB2_FULL + 8 * st, 8192);
    };
    if (lane == 0) {
#pragma unroll 1
      for (int i = 0; i < 16; i++)
#pragma unroll 1
        for (int st = w; st < 9; st += 4) {
          acquire(st, i & 1);
          asm volatile("cp.async.bulk.tensor.5d.shared::cluster.global.mbarrier::complete_tx::bytes [%0], [%1, {%3, %4, %4, %4, %5}], [%2];"
                       ::"r"(sb + S2_RING + st * 8192), "l"(&tm_xa), "r"(sb + MB2_FULL + 8 * st), "r"(st * 64), "r"(0), "r"(2 * i + par) : "memory");
        }
    }
    __syncwarp();
    uint32_t ready = 0;
#pragma unroll 1
    for (int i = 0; i < 8; i++) {
      const int blk = tq + 4 * i;
      if (!((ready >> blk) & 1)) {
        int lim = 0;
        while (true) {
          ready = __ballot_sync(~0u, ld_acquire(&g_flags[64 + lane]) >= 18);
          if (((ready >> blk) & 1) || spin_fail(++lim, SPIN_LIMIT, 1064 + blk)) break;
          __nanosleep(100);
        }
        fence_async_global();
      }
      if (lane == 0) {
#pragma unroll 1
        for (int r = 0; r < 2; r++)
#pragma unroll 1
          for (int st = w; st < 9; st += 4) {
            acquire(st, r);
            bulk_g2s(sb + S2_RING + st * 8192, hbuf + ((size_t)blk * 18 + r * 9 + st) * 8192, 8192, sb + MB2_FULL + 8 * st);
          }
      }
      __syncwarp();
    }
    ready = 0;
#pragma unroll 1
    for (int blk = 0; blk < 32; blk++) {
      if (!((ready >> blk) & 1)) {
        int lim = 0;
        while (true) {
          const uint32_t f0 = ld_acquire(&g_flags[2 * lane]), f1 = ld_acquire(&g_flags[2 * lane + 1]);
          ready = __ballot_sync(~0u, f0 >= NH && f1 >= NH);
          if (((ready >> blk) & 1) || spin_fail(++lim, SPIN_LIMIT, 1000 + blk)) break;
          __nanosleep(200);
        }
        fence_async_global();
      }
      if (lane == 0) {
#pragma unroll
        for (int r = 0; r < 4; r++) {
          const int kc = w + 4 * r, st = kc & 7;
          acquire(st, r >> 1);
          const unsigned char* src = ox + ((size_t)(2 * blk) * NH + tq * 8) * 8192 + kc * 4096;
          bulk_g2s(sb + S2_RING + st * 8192, src, 4096, sb + MB2_FULL + 8 * st);
          bulk_g2s(sb + S2_RING + st * 8192 + 4096, src + NH * 8192, 4096, sb + MB2_FULL + 8 * st);
        }
      }
      __syncwarp();
    }
    return;
  }
  if (wg == 3) {
    const int g = w;
#pragma unroll 1
    for (int i = g; i < 16; i += 2) {
      const int c = 2 * i + par;
      bar_sync(6 + g, 160);
      if (lane == 0) {
        bulk_s2g(hbuf + ((size_t)c * 18 + ct) * 8192, sb + S2_STG + g * 8192, 8192);
        bulk_commit();
        bulk_wait_read0();
        mbar_arrive(sb + MB2_STG + 8 * g);
        bulk_wait0();
        fence_async_global();
        red_release_add(&g_flags[64 + c], 1u);
      }
      __syncwarp();
    }
    return;
  }
  const bool leader = lane == 0;
  TR2(0);
  float acc[32];
  for (int i = tid; i < 64 * 72; i += 256) {
    const int m = i / 72, c = i % 72;
    const bf16* src = ((m & 8) ? b_im : b_re) + (size_t)(ct * 32 + (m >> 4) * 8 + (m & 7)) * DM + c * 8;
    cp16(sb + S2_A + (c >> 3) * 8192 + m * 128 + (((c & 7) ^ (m & 7)) << 4), src);
  }
  auto load_c = [&](int kc0, int kc1) {
    for (int i = tid; i < 64 * 8 * (kc1 - kc0); i += 256) {
      const int per = 8 * (kc1 - kc0);
      const int d = i / per, r = i % per;
      const int ri = r / (per / 2), o = r % (per / 2);
      const int kc = kc0 + (o >> 2), c8 = (o & 3) * 2 + ri;
      const bf16* src = (ri ? c_im : c_re) + (size_t)(dt * 64 + d) * DM + kc0 * 32 + o * 8;
      cp16(sb + S2_A + kc * 8192 + d * 128 + ((c8 ^ (d & 7)) << 4), src);
    }
  };
  load_c(11, 18);
  {
    for (int i = cta * 256 + tid; i < SEQ * 144; i += K2_CTAS * 256)
      *reinterpret_cast<float4*>(out + (size_t)(i / 144) * 1152 + DM + (i % 144) * 4) = make_float4(0.f, 0.f, 0.f, 0.f);
    __threadfence();
  }
  const int q = lane & 3;
  const int p = ct * 32 + w * 8 + (lane >> 2);
  float2 lam, coef;
  {
    const float lr = __bfloat162float(lam_re[p]), li = __bfloat162float(lam_im[p]);
    const float dtv = __bfloat162float(__float2bfloat16(expf(__bfloat162float(log_dt[p]))));
    const float er = expf(dtv * lr);
    float sn, cs;
    sincosf(dtv * li, &sn, &cs);
    lam = make_float2(er * cs, er * sn);
    const float nr = lam.x - 1.0f, ni = lam.y, den = lr * lr + li * li;
    coef = make_float2((nr * lr + ni * li) / den, (ni * lr - nr * li) / den);
  }
  float2 L16 = cmul(lam, lam); L16 = cmul(L16, L16); L16 = cmul(L16, L16); L16 = cmul(L16, L16);
  const float2 L32 = cmul(L16, L16), L64 = cmul(L32, L32);
  const float2 Lq = q == 0 ? make_float2(1.f, 0.f) : q == 1 ? L16 : q == 2 ? L32 : cmul(L32, L16);
  const uint32_t tag = ld_relaxed(&g_epoch);
  cp_wait_all();
  fence_async_smem();
  bar_sync(1, 256);
  if (tid == 0) red_release_add(&g_flags[96], 1u);
  TR2(1);

  float2 H = make_float2(0.f, 0.f);
  int done = -1;
#pragma unroll 1
  for (int i = wg; i < 16; i += 2) {
    const int c = 2 * i + par;
    k2_mainloop<0, 9, 9>(acc, sb, wg, leader, wg, i == 0, false);
    TR2(8 + i);
    float2 e = make_float2(acc[0], acc[2]);
#pragma unroll
    for (int u = 1; u < 16; u++) e = cfma(lam, e, make_float2(acc[4 * (u >> 1) + (u & 1)], acc[4 * (u >> 1) + 2 + (u & 1)]));
    float2 tt;
    tt.x = __shfl_up_sync(~0u, e.x, 1); tt.y = __shfl_up_sync(~0u, e.y, 1);
    if (q >= 1) e = cfma(L16, tt, e);
    tt.x = __shfl_up_sync(~0u, e.x, 2); tt.y = __shfl_up_sync(~0u, e.y, 2);
    if (q >= 2) e = cfma(L32, tt, e);
    if (q == 3) {
      asm volatile("st.relaxed.gpu.global.v2.b64 [%0], {%1, %2};" ::"l"(&g_E[c * DM + p]),
                   "l"(((uint64_t)tag << 32) | __float_as_uint(e.x)), "l"(((uint64_t)tag << 32) | __float_as_uint(e.y)) : "memory");
    }
    float2 xq, Ec;
    xq.x = __shfl_up_sync(~0u, e.x, 1); xq.y = __shfl_up_sync(~0u, e.y, 1);
    if (q == 0) xq = make_float2(0.f, 0.f);
    Ec.x = __shfl_sync(~0u, e.x, lane | 3); Ec.y = __shfl_sync(~0u, e.y, lane | 3);
    for (int cc = done + 1; cc < c; cc++) {
      uint64_t a, b; int lim = 0;
      do {
        asm volatile("ld.relaxed.gpu.global.v2.b64 {%0, %1}, [%2];" : "=l"(a), "=l"(b) : "l"(&g_E[cc * DM + p]) : "memory");
      } while (((uint32_t)(a >> 32) != tag || (uint32_t)(b >> 32) != tag) && !spin_fail(++lim, SPIN_LIMIT, 2000 + cc));
      H = cfma(L64, H, make_float2(__uint_as_float((uint32_t)a), __uint_as_float((uint32_t)b)));
    }
    __syncwarp();
    float2 sst = cfma(Lq, H, xq);
    H = cfma(L64, H, Ec);
    done = c;
    mbar_wait(sb + MB2_STG + 8 * wg, ((i >> 1) & 1) ^ 1);
    const uint32_t stg = sb + S2_STG + wg * 8192;
    const uint32_t sa = stg + ((lane >> 4) * 8 + (lane & 7)) * 128 + (((2 * w + ((lane >> 3) & 1)) ^ (lane & 7)) << 4);
#pragma unroll
    for (int j2 = 0; j2 < 4; j2++) {
      uint32_t r[4];
#pragma unroll
      for (int jj = 0; jj < 2; jj++) {
        const int j = 2 * j2 + jj;
        sst = cfma(lam, sst, make_float2(acc[4 * j], acc[4 * j + 2]));
        const float2 h0 = cmul(coef, sst);
        sst = cfma(lam, sst, make_float2(acc[4 * j + 1], acc[4 * j + 3]));
        const float2 h1 = cmul(coef, sst);
        r[2 * jj] = pack_bf16(h0.x, h1.x);
        r[2 * jj + 1] = pack_bf16(-h0.y, -h1.y);
      }
      stsm4t(sa + j2 * 2048, r[0], r[1], r[2], r[3]);
    }
    fence_async_smem();
    bar_arrive(6 + wg, 160);
  }
  mbar_wait(sb + MB2_STG + 8 * wg, 1);
  bar_sync(1, 256);
  TR2(2);
  load_c(0, 11);
  cp_wait_all();
  fence_async_smem();
  bar_sync(1, 256);
  {
    float2 dsk[8];
#pragma unroll
    for (int j = 0; j < 8; j++) {
      const uint32_t v = *reinterpret_cast<const uint32_t*>(dskip + dt * 64 + j * 8 + 2 * q);
      dsk[j] = make_float2(bf_lo(v), bf_hi(v));
    }
#pragma unroll 1
    for (int i = wg; i < 8; i += 2) {
      const int blk = tq + 4 * i;
      k2_mainloop<1, 18, 9>(acc, sb, 0, leader, wg, false, false);
      TR2(24 + i);
#pragma unroll
      for (int hh = 0; hh < 2; hh++) {
        const int n = 16 * w + 8 * hh + (lane >> 2);
        const int tok = blk * 64 + ((n >> 1) & 3) * 16 + (n >> 3) * 2 + (n & 1);
        const bf16* xr = xa + (size_t)tok * DM + dt * 64 + 2 * q;
        float* orow = out + (size_t)tok * 1152 + dt * 64 + 2 * q;
#pragma unroll
        for (int j = 0; j < 8; j++) {
          const uint32_t xv = __ldg(reinterpret_cast<const uint32_t*>(xr + j * 8));
          const uint32_t sk = pack_bf16(bf_lo(xv) * dsk[j].x, bf_hi(xv) * dsk[j].y);
          { const float2 y = make_float2(2.f * acc[4 * j + 2 * hh] + bf_lo(sk), 2.f * acc[4 * j + 2 * hh + 1] + bf_hi(sk));
            if (EF) __stcs(reinterpret_cast<float2*>(orow + j * 8), y); else *reinterpret_cast<float2*>(orow + j * 8) = y; }
        }
      }
    }
  }
  bar_sync(1, 256);
  TR2(3);
  if (tid == 0) {
    mbar_expect(sb + MB2_A, 131072);
    for (int b = 0; b < 8; b++) tma2d(sb + S2_A + b * 16384, &tm_wo, dt * 64, tq * 1024 + b * 128, sb + MB2_A);
    wait_flag(&g_flags[96], K2_CTAS);
  }
  bar_sync(1, 256);
  mbar_wait(sb + MB2_A, 0);
#pragma unroll 1
  for (int blk = wg; blk < 32; blk += 2) {
    if (PFO && w == tq) {
      const float* pf = out + (size_t)(blk * 64 + 16 * w + (lane >> 1)) * 1152 + DM + dt * 64 + (lane & 1) * 32;
      asm volatile("prefetch.global.L2 [%0];" ::"l"(pf));
    }
    k2_mainloop<2, 16, 8>(acc, sb, 0, leader, wg, false, blk == 31);
    TR2(32 + blk);
    uint32_t tn = clk32() - ((cta * 4 + w) * 37) % PACE0;
#pragma unroll
    for (int hh = 0; hh < 2; hh++) {
      float* orow = out + (size_t)(blk * 64 + 16 * w + 8 * hh + (lane >> 2)) * 1152 + DM + dt * 64 + 2 * q;
#pragma unroll
      for (int j = 0; j < 8; j++) {
        if (blk < 31) { tn += (blk < PACE_SW ? PACE0 : blk < 30 ? PACE1 : PACE0); while ((int)(clk32() - tn) < 0) __nanosleep(20); }
        asm volatile("red.relaxed.gpu.global.add.v2.f32 [%0], {%1, %2};" ::"l"(orow + j * 8), "f"(acc[4 * j + 2 * hh]), "f"(acc[4 * j + 2 * hh + 1]) : "memory");
      }
    }
  }
  TR2(4 + wg);
}
typedef CUresult (*EncodeFn)(CUtensorMap*, CUtensorMapDataType, cuuint32_t, void*, const cuuint64_t*, const cuuint64_t*,
                             const cuuint32_t*, const cuuint32_t*, CUtensorMapInterleave, CUtensorMapSwizzle,
                             CUtensorMapL2promotion, CUtensorMapFloatOOBfill);
static void make_map(EncodeFn fn, CUtensorMap* m, const void* p, int rank, const cuuint64_t* dims, const cuuint64_t* strides, const cuuint32_t* box) {
  cuuint32_t es[5] = {1, 1, 1, 1, 1};
  fn(m, CU_TENSOR_MAP_DATA_TYPE_BFLOAT16, rank, const_cast<void*>(p), dims, strides, box, es, CU_TENSOR_MAP_INTERLEAVE_NONE,
     CU_TENSOR_MAP_SWIZZLE_128B, CU_TENSOR_MAP_L2_PROMOTION_L2_128B, CU_TENSOR_MAP_FLOAT_OOB_FILL_NONE);
}

extern "C" void kernel_launch(void* const* d_in, const int* in_sizes, int n_in, void* d_out, int out_size) {
  static EncodeFn fn = nullptr;
  static void *p_ox = nullptr, *p_ar = nullptr, *p_h = nullptr;
  if (!fn) {
    cudaGetSymbolAddress(&p_ox, g_ox); cudaGetSymbolAddress(&p_ar, g_ar); cudaGetSymbolAddress(&p_h, g_h);
    void* p = nullptr;
    cudaDriverEntryPointQueryResult qr;
    cudaGetDriverEntryPoint("cuTensorMapEncodeTiled", &p, cudaEnableDefault, &qr);
    fn = (EncodeFn)p;
    cudaFuncSetAttribute(k_chain, cudaFuncAttributeMaxDynamicSharedMemorySize, K1_SMEM);
    cudaFuncSetAttribute(k_side, cudaFuncAttributeMaxDynamicSharedMemorySize, K2_SMEM);
  }
  const bf16* xa = (const bf16*)d_in[0];
  const bf16* xb = (const bf16*)d_in[9];
  CUtensorMap tx, tq, tk, tv, to, txa;
  {
    cuuint64_t d[2] = {DM, SEQ}, st[1] = {DM * 2}; cuuint32_t b[2] = {64, SEG};
    make_map(fn, &tx, xb, 2, d, st, b);
  }
  {
    cuuint64_t d[2] = {NH * DH, DM}, st[1] = {NH * DH * 2}; cuuint32_t b[2] = {64, 192};
    make_map(fn, &tq, d_in[11], 2, d, st, b); make_map(fn, &tk, d_in[12], 2, d, st, b); make_map(fn, &tv, d_in[13], 2, d, st, b);
  }
  {
    cuuint64_t d[2] = {DM, NH * DH}, st[1] = {DM * 2}; cuuint32_t b[2] = {64, 128};
    make_map(fn, &to, d_in[14], 2, d, st, b);
  }
  {
    cuuint64_t d[5] = {DM, 2, 4, 8, 32}, st[4] = {DM * 2, 16 * DM * 2, 2 * DM * 2, 64 * DM * 2}; cuuint32_t b[5] = {64, 2, 4, 8, 1};
    make_map(fn, &txa, xa, 5, d, st, b);
  }
  cudaStream_t stream = cudaStreamPerThread;
  {
    cudaLaunchConfig_t cfg = {};
    cfg.gridDim = dim3(K1_CTAS); cfg.blockDim = dim3(384); cfg.dynamicSmemBytes = K1_SMEM; cfg.stream = stream;
    cudaLaunchKernelEx(&cfg, k_chain, tx, tq, tk, tv, to, xb, (const bf16*)d_in[10], (unsigned char*)p_ox, (unsigned char*)p_ar);
  }
  {
    cudaLaunchConfig_t cfg = {};
    cfg.gridDim = dim3(K2_CTAS); cfg.blockDim = dim3(448); cfg.dynamicSmemBytes = K2_SMEM; cfg.stream = stream;
    cudaLaunchAttribute at[1];
    at[0].id = cudaLaunchAttributeProgrammaticStreamSerialization; at[0].val.programmaticStreamSerializationAllowed = 1;
    cfg.attrs = at; cfg.numAttrs = 1;
    cudaLaunchKernelEx(&cfg, k_side, txa, to, xa, (const bf16*)d_in[1], (const bf16*)d_in[2], (const bf16*)d_in[3], (const bf16*)d_in[4],
                       (const bf16*)d_in[5], (const bf16*)d_in[6], (const bf16*)d_in[7], (const bf16*)d_in[8], (float*)d_out,
                       (const unsigned char*)p_ox, (unsigned char*)p_h);
  }
}
```

```cpp
#include <cuda_runtime.h>
#include <cuda_bf16.h>
#include <cuda_fp16.h>
#include <cuda.h>
#include <stdint.h>

typedef __nv_bfloat16 bf16;
#define DEVI __device__ __forceinline__
template <int V> struct IC { static constexpr int value = V; };

DEVI uint32_t smem_u32(const void* p) { return (uint32_t)__cvta_generic_to_shared(p); }
DEVI void mbar_init(uint32_t a, uint32_t c) { asm volatile("mbarrier.init.shared::cta.b64 [%0], %1;" ::"r"(a), "r"(c) : "memory"); }
DEVI void mbar_expect(uint32_t a, uint32_t bytes) { asm volatile("mbarrier.arrive.expect_tx.shared::cta.b64 _, [%0], %1;" ::"r"(a), "r"(bytes) : "memory"); }
DEVI void mbar_arrive(uint32_t a) { asm volatile("mbarrier.arrive.shared::cta.b64 _, [%0];" ::"r"(a) : "memory"); }
#define SPIN_LIMIT (1 << 20)
#define MBAR_LIMIT (1 << 18)
DEVI bool spin_fail(int lim, int maxv, uint32_t) { if (lim > maxv) __trap(); return false; }
DEVI void mbar_wait(uint32_t a, uint32_t par) {
  uint32_t ok; int lim = 0;
  do {
    asm volatile("{.reg .pred p; mbarrier.try_wait.parity.shared::cta.b64 p, [%1], %2; selp.u32 %0,1,0,p;}" : "=r"(ok) : "r"(a), "r"(par) : "memory");
  } while (!ok && !spin_fail(++lim, MBAR_LIMIT, a));
}
DEVI void mbar_wait_fast(uint32_t a, uint32_t par) {
  asm volatile("{\n.reg .pred p, q;\n.reg .u32 c;\nmov.u32 c, 0;\n"
               "WAIT_L:\nmbarrier.try_wait.parity.shared::cta.b64 p, [%0], %1;\n"
               "add.u32 c, c, 1;\nsetp.lt.and.u32 q, c, 4194304, !p;\n@q bra.uni WAIT_L;\n@!p trap;\n}" ::"r"(a), "r"(par) : "memory");
}
DEVI bool mbar_test(uint32_t a, uint32_t par) {
  uint32_t ok;
  asm volatile("{.reg .pred p; mbarrier.test_wait.parity.shared::cta.b64 p, [%1], %2; selp.u32 %0,1,0,p;}" : "=r"(ok) : "r"(a), "r"(par) : "memory");
  return ok;
}
DEVI void mbar_wait_cl(uint32_t a, uint32_t par) {
  uint32_t ok; int lim = 0;
  do {
    asm volatile("{.reg .pred p; mbarrier.try_wait.parity.acquire.cluster.shared::cta.b64 p, [%1], %2; selp.u32 %0,1,0,p;}" : "=r"(ok) : "r"(a), "r"(par) : "memory");
  } while (!ok && !spin_fail(++lim, MBAR_LIMIT, a));
}
DEVI void bar_sync(int id, int n) { asm volatile("bar.sync %0, %1;" ::"r"(id), "r"(n) : "memory"); }
DEVI void bar_arrive(int id, int n) { asm volatile("bar.arrive %0, %1;" ::"r"(id), "r"(n) : "memory"); }
DEVI void cluster_arrive() { asm volatile("barrier.cluster.arrive.release.aligned;" ::: "memory"); }
DEVI void cluster_wait() { asm volatile("barrier.cluster.wait.acquire.aligned;" ::: "memory"); }
DEVI void fence_async_smem() { asm volatile("fence.proxy.async.shared::cta;" ::: "memory"); }
DEVI void fence_async_all() { asm volatile("fence.proxy.async;" ::: "memory"); }
DEVI void fence_async_global() { asm volatile("fence.proxy.async.global;" ::: "memory"); }
DEVI float rcp_fast(float x) { float y; asm("rcp.approx.ftz.f32 %0, %1;" : "=f"(y) : "f"(x)); return y; }
DEVI void sts128f(uint32_t a, float x, float y, float z, float w) { asm volatile("st.shared.v4.f32 [%0], {%1,%2,%3,%4};" ::"r"(a), "f"(x), "f"(y), "f"(z), "f"(w) : "memory"); }
DEVI uint32_t mapa(uint32_t a, uint32_t r) { uint32_t o; asm volatile("mapa.shared::cluster.u32 %0, %1, %2;" : "=r"(o) : "r"(a), "r"(r)); return o; }
DEVI uint32_t clk32() { uint32_t c; asm volatile("mov.u32 %0, %%clock;" : "=r"(c)::"memory"); return c; }

DEVI void spin_until(uint32_t t, const void* p) {
  asm volatile("{\n.reg .pred q;\n.reg .u64 c;\n.reg .u32 lo, hi, t2;\nmov.b64 {lo, hi}, %1;\n"
               "shr.u32 hi, hi, 31;\nand.b32 lo, lo, 1;\nadd.u32 t2, %0, hi;\nadd.u32 t2, t2, lo;\n"
               "SPIN_L:\nmov.u64 c, %%clock64;\ncvt.u32.u64 lo, c;\nsub.u32 lo, lo, t2;\nsetp.lt.s32 q, lo, 0;\n@q bra SPIN_L;\n}" ::"r"(t), "l"(p) : "memory");
}
DEVI void ldsm4(uint32_t* r, uint32_t a) { asm volatile("ldmatrix.sync.aligned.m8n8.x4.shared.b16 {%0,%1,%2,%3}, [%4];" : "=r"(r[0]), "=r"(r[1]), "=r"(r[2]), "=r"(r[3]) : "r"(a) : "memory"); }
DEVI void ldsm4t(uint32_t* r, uint32_t a) { asm volatile("ldmatrix.sync.aligned.m8n8.x4.trans.shared.b16 {%0,%1,%2,%3}, [%4];" : "=r"(r[0]), "=r"(r[1]), "=r"(r[2]), "=r"(r[3]) : "r"(a) : "memory"); }
DEVI void stsm4(uint32_t a, uint32_t r0, uint32_t r1, uint32_t r2, uint32_t r3) { asm volatile("stmatrix.sync.aligned.m8n8.x4.shared.b16 [%0], {%1,%2,%3,%4};" ::"r"(a), "r"(r0), "r"(r1), "r"(r2), "r"(r3) : "memory"); }
DEVI void stsm4t(uint32_t a, uint32_t r0, uint32_t r1, uint32_t r2, uint32_t r3) { asm volatile("stmatrix.sync.aligned.m8n8.x4.trans.shared.b16 [%0], {%1,%2,%3,%4};" ::"r"(a), "r"(r0), "r"(r1), "r"(r2), "r"(r3) : "memory"); }
DEVI void stsm2(uint32_t a, uint32_t r0, uint32_t r1) { asm volatile("stmatrix.sync.aligned.m8n8.x2.shared.b16 [%0], {%1,%2};" ::"r"(a), "r"(r0), "r"(r1) : "memory"); }
DEVI void sts64f(uint32_t a, float x, float y) { asm volatile("st.shared.v2.f32 [%0], {%1,%2};" ::"r"(a), "f"(x), "f"(y) : "memory"); }
DEVI void ldsm2(uint32_t* r, uint32_t a) { asm volatile("ldmatrix.sync.aligned.m8n8.x2.shared.b16 {%0,%1}, [%2];" : "=r"(r[0]), "=r"(r[1]) : "r"(a) : "memory"); }
DEVI uint2 lds64(uint32_t a) { uint2 v; asm volatile("ld.shared.v2.b32 {%0,%1}, [%2];" : "=r"(v.x), "=r"(v.y) : "r"(a) : "memory"); return v; }
DEVI uint2 lds64v(uint32_t a) { uint2 v; asm volatile("ld.volatile.shared.v2.b32 {%0,%1}, [%2];" : "=r"(v.x), "=r"(v.y) : "r"(a) : "memory"); return v; }
DEVI uint4 lds128(uint32_t a) { uint4 v; asm volatile("ld.shared.v4.b32 {%0,%1,%2,%3}, [%4];" : "=r"(v.x), "=r"(v.y), "=r"(v.z), "=r"(v.w) : "r"(a) : "memory"); return v; }
DEVI uint32_t opaque(uint32_t v) { return __shfl_sync(0xffffffffu, v, threadIdx.x & 31); }
DEVI uint32_t and_v(uint32_t a, uint32_t b) { uint32_t r; asm volatile("and.b32 %0, %1, %2;" : "=r"(r) : "r"(a), "r"(b)); return r; }
DEVI uint32_t half_v(uint32_t a) { uint32_t r; asm volatile("shr.u32 %0, %1, 1;" : "=r"(r) : "r"(a)); return r; }
DEVI uint32_t badd2(uint32_t a, uint32_t b) { uint32_t r; asm("add.rn.bf16x2 %0, %1, %2;" : "=r"(r) : "r"(a), "r"(b)); return r; }
DEVI uint32_t babsadd2(uint32_t a, uint32_t b) {
  __nv_bfloat162 r = __hadd2(__habs2(*reinterpret_cast<__nv_bfloat162*>(&a)), __habs2(*reinterpret_cast<__nv_bfloat162*>(&b)));
  return *reinterpret_cast<uint32_t*>(&r);
}
DEVI uint32_t babsmax2(uint32_t a, uint32_t b) {
  __nv_bfloat162 r = __hmax2(__habs2(*reinterpret_cast<__nv_bfloat162*>(&a)), __habs2(*reinterpret_cast<__nv_bfloat162*>(&b)));
  return *reinterpret_cast<uint32_t*>(&r);
}
DEVI uint32_t habsmax2(uint32_t a, uint32_t b) {
  __half2 r = __hmax2(__habs2(*reinterpret_cast<__half2*>(&a)), __habs2(*reinterpret_cast<__half2*>(&b)));
  return *reinterpret_cast<uint32_t*>(&r);
}
DEVI void sts128(uint32_t a, uint32_t x, uint32_t y, uint32_t z, uint32_t w) { asm volatile("st.shared.v4.b32 [%0], {%1,%2,%3,%4};" ::"r"(a), "r"(x), "r"(y), "r"(z), "r"(w) : "memory"); }
DEVI void sts64(uint32_t a, uint32_t x, uint32_t y) { asm volatile("st.shared.v2.b32 [%0], {%1,%2};" ::"r"(a), "r"(x), "r"(y) : "memory"); }
DEVI void sts32(uint32_t a, uint32_t v) { asm volatile("st.shared.b32 [%0], %1;" ::"r"(a), "r"(v) : "memory"); }
DEVI uint32_t lds32(uint32_t a) { uint32_t v; asm volatile("ld.shared.b32 %0, [%1];" : "=r"(v) : "r"(a) : "memory"); return v; }
DEVI float2 lds64f(uint32_t a) { float2 v; asm volatile("ld.shared.v2.f32 {%0,%1}, [%2];" : "=f"(v.x), "=f"(v.y) : "r"(a) : "memory"); return v; }
DEVI float4 lds128f(uint32_t a) { float4 v; asm volatile("ld.shared.v4.f32 {%0,%1,%2,%3}, [%4];" : "=f"(v.x), "=f"(v.y), "=f"(v.z), "=f"(v.w) : "r"(a) : "memory"); return v; }

DEVI void mma16(float* d, const uint32_t* a, uint32_t b0, uint32_t b1) {
  asm volatile("mma.sync.aligned.m16n8k16.row.col.f32.bf16.bf16.f32 {%0,%1,%2,%3}, {%4,%5,%6,%7}, {%8,%9}, {%0,%1,%2,%3};"
               : "+f"(d[0]), "+f"(d[1]), "+f"(d[2]), "+f"(d[3]) : "r"(a[0]), "r"(a[1]), "r"(a[2]), "r"(a[3]), "r"(b0), "r"(b1));
}
DEVI void mma16r(float* d, uint32_t a0, uint32_t a1, uint32_t a2, uint32_t a3, uint32_t b0, uint32_t b1) {
  asm volatile("mma.sync.aligned.m16n8k16.row.col.f32.bf16.bf16.f32 {%0,%1,%2,%3}, {%4,%5,%6,%7}, {%8,%9}, {%0,%1,%2,%3};"
               : "+f"(d[0]), "+f"(d[1]), "+f"(d[2]), "+f"(d[3]) : "r"(a0), "r"(a1), "r"(a2), "r"(a3), "r"(b0), "r"(b1));
}
DEVI void mma16z(float* d, uint32_t a0, uint32_t a1, uint32_t a2, uint32_t a3, uint32_t b0, uint32_t b1) {
  asm volatile("mma.sync.aligned.m16n8k16.row.col.f32.bf16.bf16.f32 {%0,%1,%2,%3}, {%4,%5,%6,%7}, {%8,%9}, {%10,%10,%10,%10};"
               : "=f"(d[0]), "=f"(d[1]), "=f"(d[2]), "=f"(d[3]) : "r"(a0), "r"(a1), "r"(a2), "r"(a3), "r"(b0), "r"(b1), "f"(0.f));
}
DEVI void mma8(float* d, uint32_t a0, uint32_t a1, uint32_t b0) {
  asm volatile("mma.sync.aligned.m16n8k8.row.col.f32.bf16.bf16.f32 {%0,%1,%2,%3}, {%4,%5}, {%6}, {%0,%1,%2,%3};"
               : "+f"(d[0]), "+f"(d[1]), "+f"(d[2]), "+f"(d[3]) : "r"(a0), "r"(a1), "r"(b0));
}
DEVI void mma8z(float* d, uint32_t a0, uint32_t a1, uint32_t b0) {
  asm volatile("mma.sync.aligned.m16n8k8.row.col.f32.bf16.bf16.f32 {%0,%1,%2,%3}, {%4,%5}, {%6}, {%7,%7,%7,%7};"
               : "=f"(d[0]), "=f"(d[1]), "=f"(d[2]), "=f"(d[3]) : "r"(a0), "r"(a1), "r"(b0), "f"(0.f));
}
DEVI uint32_t pack_bf16(float lo, float hi) { uint32_t r; asm("cvt.rn.bf16x2.f32 %0, %1, %2;" : "=r"(r) : "f"(hi), "f"(lo)); return r; }
DEVI uint32_t pack_f16(float lo, float hi) { uint32_t r; asm("cvt.rn.f16x2.f32 %0, %1, %2;" : "=r"(r) : "f"(hi), "f"(lo)); return r; }
DEVI uint32_t pack_f16_sat(float lo, float hi) { uint32_t r; asm("cvt.rn.satfinite.f16x2.f32 %0, %1, %2;" : "=r"(r) : "f"(hi), "f"(lo)); return r; }
DEVI uint32_t h2b(uint32_t h) { float2 f = __half22float2(*reinterpret_cast<const __half2*>(&h)); return pack_bf16(f.x, f.y); }
DEVI float ex2(float x) { float y; asm("ex2.approx.ftz.f32 %0, %1;" : "=f"(y) : "f"(x)); return y; }
DEVI float bf_lo(uint32_t v) { return __uint_as_float(v << 16); }
DEVI float bf_hi(uint32_t v) { return __uint_as_float(v & 0xffff0000u); }

DEVI void st_async32(uint32_t a, uint32_t v, uint32_t mb) { asm volatile("st.async.shared::cluster.mbarrier::complete_tx::bytes.b32 [%0], %1, [%2];" ::"r"(a), "r"(v), "r"(mb) : "memory"); }
DEVI void st_async64(uint32_t a, uint32_t x, uint32_t y, uint32_t mb) { asm volatile("st.async.shared::cluster.mbarrier::complete_tx::bytes.v2.b32 [%0], {%1,%2}, [%3];" ::"r"(a), "r"(x), "r"(y), "r"(mb) : "memory"); }
DEVI void st_async64f(uint32_t a, float x, float y, uint32_t mb) { asm volatile("st.async.shared::cluster.mbarrier::complete_tx::bytes.v2.f32 [%0], {%1,%2}, [%3];" ::"r"(a), "f"(x), "f"(y), "r"(mb) : "memory"); }
DEVI void st_async128f(uint32_t a, float x, float y, float z, float w, uint32_t mb) { asm volatile("st.async.shared::cluster.mbarrier::complete_tx::bytes.v4.f32 [%0], {%1,%2,%3,%4}, [%5];" ::"r"(a), "f"(x), "f"(y), "f"(z), "f"(w), "r"(mb) : "memory"); }

DEVI void tma2d(uint32_t dst, const CUtensorMap* m, int c0, int c1, uint32_t mb) {
  asm volatile("cp.async.bulk.tensor.2d.shared::cluster.global.mbarrier::complete_tx::bytes [%0], [%1, {%3, %4}], [%2];"
               ::"r"(dst), "l"(m), "r"(mb), "r"(c0), "r"(c1) : "memory");
}
DEVI uint64_t policy_evict_first() { uint64_t p; asm volatile("createpolicy.fractional.L2::evict_first.b64 %0, 1.0;" : "=l"(p)); return p; }
DEVI void tma2d_hint(uint32_t dst, const CUtensorMap* m, int c0, int c1, uint32_t mb, uint64_t pol) {
  asm volatile("cp.async.bulk.tensor.2d.shared::cluster.global.mbarrier::complete_tx::bytes.L2::cache_hint [%0], [%1, {%3, %4}], [%2], %5;"
               ::"r"(dst), "l"(m), "r"(mb), "r"(c0), "r"(c1), "l"(pol) : "memory");
}
DEVI void tma2d_mc(uint32_t dst, const CUtensorMap* m, int c0, int c1, uint32_t mb, uint16_t mask) {
  asm volatile("cp.async.bulk.tensor.2d.shared::cluster.global.mbarrier::complete_tx::bytes.multicast::cluster [%0], [%1, {%3, %4}], [%2], %5;"
               ::"r"(dst), "l"(m), "r"(mb), "r"(c0), "r"(c1), "h"(mask) : "memory");
}
DEVI void tma2d_prefetch(const CUtensorMap* m, int c0, int c1) {
  asm volatile("cp.async.bulk.prefetch.tensor.2d.L2.global [%0, {%1, %2}];" ::"l"(m), "r"(c0), "r"(c1) : "memory");
}
DEVI void bulk_g2s(uint32_t dst, const void* src, uint32_t bytes, uint32_t mb) {
  asm volatile("cp.async.bulk.shared::cluster.global.mbarrier::complete_tx::bytes [%0], [%1], %2, [%3];" ::"r"(dst), "l"(src), "r"(bytes), "r"(mb) : "memory");
}
DEVI void bulk_s2c(uint32_t dst, uint32_t src, uint32_t bytes, uint32_t mb) {
  asm volatile("cp.async.bulk.shared::cluster.shared::cta.mbarrier::complete_tx::bytes [%0], [%1], %2, [%3];" ::"r"(dst), "r"(src), "r"(bytes), "r"(mb) : "memory");
}
DEVI void bulk_s2g(void* dst, uint32_t src, uint32_t bytes) {
  asm volatile("cp.async.bulk.global.shared::cta.bulk_group [%0], [%1], %2;" ::"l"(dst), "r"(src), "r"(bytes) : "memory");
}
DEVI void bulk_commit() { asm volatile("cp.async.bulk.commit_group;" ::: "memory"); }
DEVI void bulk_wait0() { asm volatile("cp.async.bulk.wait_group 0;" ::: "memory"); }
DEVI void bulk_wait_read0() { asm volatile("cp.async.bulk.wait_group.read 0;" ::: "memory"); }

DEVI uint4 ld_relaxed_v4(const void* p) { uint4 v; asm volatile("ld.relaxed.gpu.global.v4.u32 {%0,%1,%2,%3}, [%4];" : "=r"(v.x), "=r"(v.y), "=r"(v.z), "=r"(v.w) : "l"(p) : "memory"); return v; }
DEVI uint2 ld_relaxed_v2(const void* p) { uint2 v; asm volatile("ld.relaxed.gpu.global.v2.u32 {%0,%1}, [%2];" : "=r"(v.x), "=r"(v.y) : "l"(p) : "memory"); return v; }
DEVI void st_relaxed_v4(void* p, uint32_t a, uint32_t b, uint32_t c, uint32_t d) { asm volatile("st.relaxed.gpu.global.v4.u32 [%0], {%1,%2,%3,%4};" ::"l"(p), "r"(a), "r"(b), "r"(c), "r"(d) : "memory"); }
DEVI uint32_t ld_acquire(const uint32_t* p) { uint32_t v; asm volatile("ld.acquire.gpu.global.u32 %0, [%1];" : "=r"(v) : "l"(p) : "memory"); return v; }
DEVI uint32_t ld_relaxed(const uint32_t* p) { uint32_t v; asm volatile("ld.relaxed.gpu.global.u32 %0, [%1];" : "=r"(v) : "l"(p) : "memory"); return v; }
DEVI void red_release_add(uint32_t* p, uint32_t v) { asm volatile("red.release.gpu.global.add.u32 [%0], %1;" ::"l"(p), "r"(v) : "memory"); }
DEVI void red_relaxed_add(uint32_t* p, uint32_t v) { asm volatile("red.relaxed.gpu.global.add.u32 [%0], %1;" ::"l"(p), "r"(v) : "memory"); }
DEVI void red_f16x8(void* p, uint32_t a, uint32_t b, uint32_t c, uint32_t d) {
  asm volatile("red.relaxed.gpu.global.add.noftz.v4.f16x2 [%0], {%1,%2,%3,%4};" ::"l"(p), "r"(a), "r"(b), "r"(c), "r"(d) : "memory");
}

DEVI void cp16(uint32_t dst, const void* src) { asm volatile("cp.async.cg.shared.global [%0], [%1], 16;" ::"r"(dst), "l"(src) : "memory"); }
DEVI void cp_wait_all() { asm volatile("cp.async.wait_all;" ::: "memory"); }
#define WG_FENCE() asm volatile("wgmma.fence.sync.aligned;" ::: "memory")
#define WG_COMMIT() asm volatile("wgmma.commit_group.sync.aligned;" ::: "memory")
#define WG_WAIT(n) asm volatile("wgmma.wait_group.sync.aligned %0;" ::"n"(n) : "memory")
DEVI uint64_t mkdesc(uint32_t saddr, uint32_t lbo, uint32_t sbo) {
  return (uint64_t)((saddr & 0x3FFFF) >> 4) | ((uint64_t)(lbo >> 4) << 16) | ((uint64_t)(sbo >> 4) << 32) | (1ull << 62);
}
DEVI uint32_t desc_lo(uint32_t saddr) { return ((saddr & 0x3FFFF) >> 4) | (1u << 16); }
DEVI uint64_t desc64(uint32_t lo) { uint64_t d; asm("mov.b64 %0, {%1, %2};" : "=l"(d) : "r"(lo), "r"(0x40000040u)); return d; }
DEVI void wg_n32_rs(float* d, const uint32_t* a, uint64_t db, int sc) {
  asm volatile("{.reg .pred p; setp.ne.b32 p, %21, 0;\n"
               "wgmma.mma_async.sync.aligned.m64n32k16.f32.bf16.bf16 {%0,%1,%2,%3,%4,%5,%6,%7,%8,%9,%10,%11,%12,%13,%14,%15}, {%16,%17,%18,%19}, %20, p, 1, 1, 0;}\n"
               : "+f"(d[0]), "+f"(d[1]), "+f"(d[2]), "+f"(d[3]), "+f"(d[4]), "+f"(d[5]), "+f"(d[6]), "+f"(d[7]),
                 "+f"(d[8]), "+f"(d[9]), "+f"(d[10]), "+f"(d[11]), "+f"(d[12]), "+f"(d[13]), "+f"(d[14]), "+f"(d[15])
               : "r"(a[0]), "r"(a[1]), "r"(a[2]), "r"(a[3]), "l"(db), "r"(sc));
}
DEVI void wg_n32_ss_ta(float* d, uint64_t da, uint64_t db, int sc) {
  asm volatile("{.reg .pred p; setp.ne.b32 p, %18, 0;\n"
               "wgmma.mma_async.sync.aligned.m64n32k16.f32.bf16.bf16 {%0,%1,%2,%3,%4,%5,%6,%7,%8,%9,%10,%11,%12,%13,%14,%15}, %16, %17, p, 1, 1, 1, 0;}\n"
               : "+f"(d[0]), "+f"(d[1]), "+f"(d[2]), "+f"(d[3]), "+f"(d[4]), "+f"(d[5]), "+f"(d[6]), "+f"(d[7]),
                 "+f"(d[8]), "+f"(d[9]), "+f"(d[10]), "+f"(d[11]), "+f"(d[12]), "+f"(d[13]), "+f"(d[14]), "+f"(d[15])
               : "l"(da), "l"(db), "r"(sc));
}
DEVI void wg_n32_rs_z(float* d, const uint32_t* a, uint64_t db) {
  asm volatile("{.reg .pred p; setp.ne.b32 p, 0, 0;\n"
               "wgmma.mma_async.sync.aligned.m64n32k16.f32.bf16.bf16 {%0,%1,%2,%3,%4,%5,%6,%7,%8,%9,%10,%11,%12,%13,%14,%15}, {%16,%17,%18,%19}, %20, p, 1, 1, 0;}\n"
               : "=f"(d[0]), "=f"(d[1]), "=f"(d[2]), "=f"(d[3]), "=f"(d[4]), "=f"(d[5]), "=f"(d[6]), "=f"(d[7]),
                 "=f"(d[8]), "=f"(d[9]), "=f"(d[10]), "=f"(d[11]), "=f"(d[12]), "=f"(d[13]), "=f"(d[14]), "=f"(d[15])
               : "r"(a[0]), "r"(a[1]), "r"(a[2]), "r"(a[3]), "l"(db));
}
constexpr int DM = 576, NH = 32, DH = 128, SEG = 32, NSEG = 64, SEQ = 2048;
constexpr int K1_CTAS = 96;

__device__ __align__(131072) unsigned char g_ar[4 * 24576 + 2048];
__device__ __align__(1024) unsigned char g_ox[NSEG * NH * 8192];
__device__ unsigned long long g_pub[96];
__device__ __align__(256) uint32_t g_flags[128];
__device__ uint32_t g_epoch;
#define TR(i)
#define TRP(i)
#define TRV(i, v)
#define TRDUMP()
#define TRG(i)

constexpr uint32_t SM_XB = 0;
constexpr uint32_t SM_W = 73728;
#define KSS 5
constexpr int KS_SM = KSS;
constexpr uint32_t SM_WO = SM_W + 10240;
constexpr uint32_t SM_ST1 = SM_WO + 36864;
constexpr uint32_t SM_VM = SM_WO + 45056;
constexpr uint32_t SM_QM = SM_VM + 8192;
constexpr uint32_t SM_SB = SM_QM + 2048;
constexpr uint32_t SM_OT = SM_SB + 2560;
constexpr uint32_t SM_PX = SM_W + 73728 + 10240;
constexpr uint32_t SM_VX = SM_PX + 32768;
constexpr uint32_t SM_OS = SM_VX;
constexpr uint32_t SM_ST0 = SM_VX + 16384;
constexpr uint32_t SM_PT = SM_ST0;
static_assert(SM_OT + 2048 <= SM_W + 73728, "alias overflow");
constexpr uint32_t SM_MEMB = SM_W + 147456;
constexpr uint32_t SM_MISC = SM_MEMB + 9216;
constexpr uint32_t MB_W = SM_MISC;
constexpr uint32_t MB_WO = SM_MISC + 24;
constexpr uint32_t MB_XT = SM_MISC + 32;
constexpr uint32_t MB_X = SM_MISC + 88;
constexpr uint32_t MB_V = SM_MISC + 56;
constexpr uint32_t MB_ST = SM_MISC + 72;
constexpr uint32_t SM_MX = SM_MISC + 96;
constexpr uint32_t SM_ISC = SM_MISC + 112;
constexpr uint32_t SM_ZERO = SM_MISC + 200;
constexpr uint32_t SM_G = SM_MISC + 204;
constexpr uint32_t SM_RED = SM_MISC + 128;
constexpr uint32_t SM_TP = SM_MISC + 208;
constexpr uint32_t SM_XMAX = SM_MISC + 256;
constexpr uint32_t SM_HINT = SM_OT + 2048;
static_assert(SM_HINT + 192 <= SM_W + 73728, "alias");
constexpr uint32_t SM_TRC = SM_MISC + 512;
constexpr uint32_t K1_SMEM = SM_MISC + 512;
static_assert(SM_PT + 10240 <= SM_MEMB, "alias overflow");
static_assert(K1_SMEM <= 232448, "smem");

enum { BAR_MEM = 1, BAR_QK = 2, BAR_O = 3, BAR_HK = 5, BAR_B = 6, BAR_GO = 7   };
DEVI uint32_t ar_off(int s) { return ((s >> 1) & 3) * 24576 + (s & 1) * 128; }
DEVI uint32_t hint_off(int s) { return 4 * 24576 + (s & 7) * 256; }
DEVI uint32_t xbuf(int b) { return b == 2 ? SM_WO : SM_XB + b * 36864; }
#define EXP_KS 36
#define APRE 16
#define SSPOS 9
#define HINTS 1
#define GOCUT 1
#define PIN (!GOCUT)
#define VAPOS 2
#define VAD 560
#define HFPOS 1
#define EF 1
#define WPF 1
#define SMX_EARLY 1
#define TOK7 1
#define NB (SMX_EARLY ? 192 : 256)
#define PF0 4
#define PFD 6
#define CUT 0
#define VXD 150
#define NCH 2
#define KPRE 1
#define FINE 1
#define SCUT 3
#define HRW 7
#define FPIN 1
#define DSIMP 0
#define STAG 0
#define SF16 1
#define SBB (SF16 ? 640 : 1280)
#define CUTE 12
#define STPRE 0
#define QKP 1
#define PRETRY 0
#define VXB 0
#define DELAY0 0
#define DELAY1 0
#define WARM 0
#define LDEP -1
#define PD0 0
#define STG0 1200
#define XC 1
#define WOP 0
#define XPOS 0
#define POLL_DELAY 2500
#define R2SLACK 3
#define HW 3

DEVI float warp_max_nn(float v) { return __uint_as_float(__reduce_max_sync(0xffffffffu, __float_as_uint(v))); }

DEVI int hint_max(uint2 hv, uint32_t own) {
  const uint32_t o = own << 17;
  const int d0 = (int)((hv.x << 17) - o), d1 = (int)((hv.x << 1) - o), d2 = (int)((hv.y << 17) - o), d3 = (int)((hv.y << 1) - o);
  int d = max(max(d0, d1), max(d2, d3)) >> 17;
  return __reduce_max_sync(0xffffffffu, d);
}

__global__ void __cluster_dims__(3, 1, 1) __launch_bounds__(384, 1)
k_chain(const __grid_constant__ CUtensorMap tm_x, const __grid_constant__ CUtensorMap tm_wq,
        const __grid_constant__ CUtensorMap tm_wk, const __grid_constant__ CUtensorMap tm_wv,
        const __grid_constant__ CUtensorMap tm_wo, const bf16* __restrict__ xg, const bf16* __restrict__ mem0,
        unsigned char* __restrict__ ox, unsigned char* __restrict__ arb) {
  extern __shared__ __align__(1024) unsigned char smem[];
  const uint32_t sb = smem_u32(smem);
  const int tid = threadIdx.x, lane = tid & 31;
  const int wid = __shfl_sync(0xffffffffu, tid >> 5, 0), wg = wid >> 2, w = wid & 3;
  const int rank = blockIdx.x % 3, head = blockIdx.x / 3;
  const float SCL = 0.08838834764831845f * 1.4426950408889634f;

  if (tid == 0) TRG(8);
  const uint32_t dl0 = 0u - ((uint32_t)rank << 24), dl1 = dl0 + (1u << 24), dl2 = dl0 + (2u << 24);
  if (mapa(sb, 0) != sb + dl0 || mapa(sb, 1) != sb + dl1 || mapa(sb, 2) != sb + dl2) __trap();

  auto send_vx = [&](int g, uint32_t dl) {
    fence_async_smem();
    bulk_s2c(sb + dl + SM_VX + (g & 1) * 8192, sb + SM_PX + (g & 3) * 8192, 8192, sb + dl + MB_V + 8 * (g & 1));
  };
  auto load_x = [&](int g, int b) {
    mbar_expect(sb + MB_XT + 8 * b, 36864);
#pragma unroll
    for (int c = 0; c < 3; c++) {
      const int kc = rank * 3 + c;
      tma2d_mc(sb + xbuf(b) + kc * 4096, &tm_x, kc * 64, g * SEG, sb + MB_XT + 8 * b, (uint16_t)7);
    }
  };
  if (wg < 2) {
    if (KSS < 5) asm volatile("setmaxnreg.inc.sync.aligned.u32 176;");
    asm volatile("barrier.cluster.arrive.relaxed.aligned;" ::: "memory");
    {
      uint4 mv[3];
#pragma unroll
    for (int i = 0; i < 3; i++) mv[i] = __ldg(reinterpret_cast<const uint4*>(mem0) + min(i * 256 + tid, 575));
    if (tid == 0 && blockIdx.x < NSEG)
      asm volatile("cp.async.bulk.prefetch.L2.global [%0], %1;" ::"l"(xg + (size_t)blockIdx.x * SEG * DM), "r"(SEG * DM * 2) : "memory");
      bar_sync(0, 384);
      if (lane == 0 && w < 3) {
        const CUtensorMap* m = rank == 2 ? &tm_wv : wg ? &tm_wk : &tm_wq;
        const int col = head * DH + (rank == 2 ? wg : rank) * 64;
        if (DELAY0) __nanosleep(DELAY0);
        if (STG0) __nanosleep(STG0 * w);
        if (WPF) tma2d_prefetch(m, col, w * 192);
        tma2d_hint(sb + SM_W + wg * 73728 + w * 24576, m, col, w * 192, sb + MB_W + 8 * w, policy_evict_first());
      }
      if (wid == 3) {
        reinterpret_cast<uint4*>(arb)[blockIdx.x * 32 + lane] = make_uint4(0, 0, 0, 0);
        if (blockIdx.x == 93 || blockIdx.x == 94) reinterpret_cast<uint4*>(arb + 4 * 24576)[(blockIdx.x - 93) * 32 + lane] = make_uint4(0, 0, 0, 0);
        if (blockIdx.x == 95) reinterpret_cast<uint4*>(g_flags)[lane] = make_uint4(0, 0, 0, 0);
        __threadfence();
      }
      __syncwarp();
      if (tid == 0) TRG(9);
      uint32_t mx = 0;
#pragma unroll
      for (int i = 0; i < 3; i++) {
        const int v = min(i * 256 + tid, 575), r = v / 72, c = (v % 72) * 8;
        const uint32_t a[4] = {mv[i].x, mv[i].y, mv[i].z, mv[i].w};
#pragma unroll
        for (int j = 0; j < 4; j++) {
          *reinterpret_cast<unsigned short*>(smem + SM_MEMB + (c + 2 * j) * 16 + r * 2) = (unsigned short)a[j];
          *reinterpret_cast<unsigned short*>(smem + SM_MEMB + (c + 2 * j + 1) * 16 + r * 2) = (unsigned short)(a[j] >> 16);
          mx = babsmax2(mx, a[j]);
        }
      }
      mx = __reduce_max_sync(0xffffffffu, max(mx & 0xffffu, mx >> 16));
      sts32(sb + SM_XMAX + wid * 4, mx << 16);
    }
    if (tid == 0) TRG(10);
    uint32_t A[36][4];
    const uint32_t wofs = sb + SM_W + wg * 73728 + (((lane >> 4) * 8 + (lane & 7)) * 128 + (((2 * w + ((lane >> 3) & 1)) ^ (lane & 7)) << 4));
    {
      float nn[4][4];
#pragma unroll 1
      for (int pass = WARM ? 0 : 1; pass < 2; pass++) {
#pragma unroll
        for (int i = 0; i < 16; i++) nn[i >> 2][i & 3] = 0.f;
#pragma unroll
        for (int ks = 0; ks < 36; ks++) {
          if (ks % 12 == 0 && pass) mbar_wait(sb + MB_W + 8 * (ks / 12), 0);
          if (ks % 12 == 0 && tid == 0) TRG(11 + ks / 12);
          ldsm4t(A[ks], wofs + ks * 2048);
          mma16r(nn[ks & 3], A[ks][0] & 0x7fff7fffu, A[ks][1] & 0x7fff7fffu, A[ks][2] & 0x7fff7fffu, A[ks][3] & 0x7fff7fffu, 0x3f803f80u, 0x3f803f80u);
        }
      }
      sts32(sb + SM_RED + wid * 4, __float_as_uint(warp_max_nn(fmaxf((nn[0][0] + nn[1][0]) + (nn[2][0] + nn[3][0]), (nn[0][2] + nn[1][2]) + (nn[2][2] + nn[3][2])))));
    }
    if (tid == 0) TRG(14);
    asm volatile("barrier.cluster.wait.aligned;" ::: "memory");
    bar_arrive(BAR_HK, 384);
    bar_sync(BAR_QK, 256);
    if (tid == 0) TRG(1);
    asm volatile("barrier.cluster.arrive.relaxed.aligned;" ::: "memory");
    if (LDEP < 0) asm volatile("griddepcontrol.launch_dependents;" ::: "memory");

    const uint32_t l16 = opaque(sb + lane * 16);
    const uint32_t wofs2 = WOP ? opaque(wofs) : 0;
    int xb = 0, xc = 0, xph = 0;
    auto load_a = [&]() {
#pragma unroll
      for (int ks = 0; ks < KS_SM; ks++) ldsm4t(A[ks], (WOP ? wofs2 : wofs) + ks * 2048);
    };
    auto filler_mma = [&](float* acc, uint32_t xo, auto K0, auto K1, auto hook) {
      const uint64_t d0 = DSIMP ? desc64(desc_lo(sb + xo)) : mkdesc(sb + xo, 16, 1024), dW = desc64(desc_lo(sb + SM_W + wg * 73728));
      if (APRE == 2) load_a();
      WG_FENCE();
#pragma unroll
      for (int i = K0.value; i < K1.value; i++) {
        const int ks = i < SSPOS ? i + KS_SM : i < SSPOS + KS_SM ? i - SSPOS : i;
        const uint64_t db = d0 + (uint64_t)(((ks >> 2) * 4096 + (ks & 3) * 32) >> 4);
        if (ks < KS_SM) wg_n32_ss_ta(acc, DSIMP ? dW + ks * 128 : mkdesc(sb + SM_W + wg * 73728 + ks * 2048, 16, 1024), db, 1);
        else if (i == 0) wg_n32_rs_z(acc, A[ks], db);
        else wg_n32_rs(acc, A[ks], db, 1);
        if (APRE >= 10 && i == APRE - 10) { WG_COMMIT(); WG_WAIT(1); load_a(); }
        if (APRE >= 10 && i == APRE - 14) WG_COMMIT();
      }
      WG_COMMIT();
      hook();
      if (APRE == 1) load_a();
      WG_WAIT(0);
    };
    auto nop = []() {};
    auto go = [&]() {
      if (GOCUT == 2) bar_sync(BAR_GO, 384); else bar_sync(BAR_GO + wg, 256);
      if (STAG && wg == 0) __nanosleep(STAG);
    };
    auto x_wait = [&]() { mbar_wait(sb + MB_XT + 8 * xb, XC ? xc >= 3 : xph); };
    auto x_next = [&]() { if (XC) { xc = xc == 5 ? 0 : xc + 1; xb = xc >= 3 ? xc - 3 : xc; } else if (++xb == 3) { xb = 0; xph ^= 1; } };
    auto mem_proj = [&](int s, float mul, uint32_t& lo, uint32_t& hi, auto pre) {
      if (!APRE) load_a();
      bar_sync(BAR_MEM, 384);
      float c[NCH][4];
      uint32_t b[18][4];
#pragma unroll
      for (int i = 0; i < PF0; i++) ldsm4t(b[i], l16 + SM_MEMB + i * 512);
      if (CUT) { if (xb == 77) __trap(); }
      int nl = PF0;
#pragma unroll
      for (int k2 = 0; k2 < 18; k2++) {
        const int ka = 2 * k2, kb = 2 * k2 + 1;
        if (ka < NCH) mma16z(c[ka], A[ka][0], A[ka][1], A[ka][2], A[ka][3], b[k2][0], b[k2][1]); else mma16(c[ka % NCH], A[ka], b[k2][0], b[k2][1]);
        if (kb < NCH) mma16z(c[kb], A[kb][0], A[kb][1], A[kb][2], A[kb][3], b[k2][2], b[k2][3]); else mma16(c[kb % NCH], A[kb], b[k2][2], b[k2][3]);
        const int want = k2 + 1 + (k2 < 2 ? PF0 : PFD);
#pragma unroll
        for (int i = 0; i < 18; i++) if (i >= nl && i < want) ldsm4t(b[i], l16 + SM_MEMB + i * 512);
        nl = want > nl ? want : nl;
        if (CUT > 1 && k2 % (CUT ? CUT : 1) == CUT - 1 && k2 < CUTE) { if (xb == 78 + k2) __trap(); }
        if (k2 == 15) pre();
      }
      const float isc = __uint_as_float(lds32(sb + SM_ISC + (s & 1) * 8)) * mul;
      float r[4];
#pragma unroll
      for (int i = 0; i < 4; i++) r[i] = NCH == 4 ? (c[0][i] + c[1][i]) + (c[2 % NCH][i] + c[NCH - 1][i]) : NCH == 3 ? c[0][i] + c[1][i] + c[2 % NCH][i] : c[0][i] + c[1][i];
      lo = pack_bf16(r[0] * isc, r[1] * isc);
      hi = pack_bf16(r[2] * isc, r[3] * isc);
    };
    auto hint_fetch = [&](int s) {
      if (and_v(l16, 496u) < 192u) cp16(l16 + SM_HINT, arb + hint_off(s) + and_v(l16, 496u));
    };
    auto hint_read = [&](int s) {
      const uint32_t ho = min(and_v(l16, 496u), 368u) >> 1;
      int dm, lim = 0;
      cp_wait_all();
      __syncwarp();
      uint2 hv = lds64(sb + SM_HINT + ho);
      while (__any_sync(0xffffffffu, (hv.x & hv.y & 0x80008000u) != 0x80008000u) && !spin_fail(++lim, SPIN_LIMIT, 300 + s))
        hv = ld_relaxed_v2(arb + hint_off(s) + ho);
      const uint2 own = lds64v(sb + SM_TP);
      dm = hint_max(hv, own.x);
      TRV(3, dm + 100); TR(7);
      sts64(sb + SM_TP + 8, s + 1, own.y + POLL_DELAY + (s == 0 ? PD0 : 0) + ((min(dm, 160) * 29) >> 2) * HINTS);
    };
    if (rank < 2) {
      auto epilogue = [&](const float* acc, int g) {
        const uint32_t dst = l16 + SM_PX + (g & 3) * 8192 + wg * 4096 + w * 512;
        stsm4(dst, pack_bf16(acc[0], acc[1]), pack_bf16(acc[4], acc[5]), pack_bf16(acc[2], acc[3]), pack_bf16(acc[6], acc[7]));
        stsm4(dst + 2048, pack_bf16(acc[8], acc[9]), pack_bf16(acc[12], acc[13]), pack_bf16(acc[10], acc[11]), pack_bf16(acc[14], acc[15]));
      };
#pragma unroll 1
      for (int g = 0; g < 2; g++) { float acc[16]; x_wait(); if (tid == 0) TRG(20 + g); filler_mma(acc, xbuf(xb), IC<0>{}, IC<36>{}, nop); x_next(); if (g == 0) cluster_wait(); epilogue(acc, g); }
      if (APRE == 3) load_a();
      if (tid == 0) TRG(2);
      const uint32_t dO = rank ? dl0 : dl1;
#pragma unroll 1
      for (int s = 0; s <= NSEG; s++) {
        const uint32_t pxo = SM_PX + (s & 3) * 8192;
        auto st_wait = [&]() { if (wg) mbar_wait(sb + MB_ST + 8 * (s & 1), (s >> 1) & 1); };
        auto tok_pair = [&](const uint32_t* k, int mt, int p) {
          const uint32_t qa = l16 + pxo + mt * 2048;
          uint32_t a[4][4];
          ldsm4t(a[0], qa); ldsm4t(a[1], qa + 512); ldsm4t(a[2], qa + 1024); ldsm4t(a[3], qa + 1536);
          float d[4], e[4];
          mma16z(d, a[0][0], a[0][1], a[0][2], a[0][3], k[0], k[1]);
          mma16z(e, a[1][0], a[1][1], a[1][2], a[1][3], k[2], k[3]);
          mma16(d, a[2], k[4], k[5]);
          mma16(e, a[3], k[6], k[7]);
          const uint32_t sta = half_v(l16 + sb) + SM_ST0 + (s & 1) * 4096 + p * 512;
          sts64f(sta, (d[0] + e[0]) * SCL, (d[1] + e[1]) * SCL); sts64f(sta + 256, (d[2] + e[2]) * SCL, (d[3] + e[3]) * SCL);
        };
        if (s < NSEG) {
          uint32_t lo, hi, q[8], k[8];
          const int j = wg ? 0 : w + 1;
          const uint32_t kxo = pxo + 4096 + (wg ? 0 : (w >> 1) * 2048 + (w & 1) * 128);
          mem_proj(s, wg ? 1.0f : SCL, lo, hi, [&]() { const uint32_t kx = l16 + and_v(l16, 384u) + kxo; ldsm4t(k, kx); ldsm4t(k + 4, kx + 1024); });
          TR(2);
          stsm2(l16 + and_v(l16, wg ? 0u : 128u) + SM_QM + (wg ? 1024 + w * 256 : (w >> 1) * 512 + (w & 1) * 128), lo, hi);
          if (QKP) asm volatile("{.reg .pred p; setp.lt.s32 p, %0, 5; @p bar.sync 2, 256; @!p bar.arrive 2, 256;}" ::"r"(wid) : "memory");
          else bar_sync(BAR_QK, 256);
          if (wid < 5) {
            ldsm4t(q, l16 + SM_QM);
            if (wg) ldsm4t(k, l16 + SM_QM + 1024);
            ldsm4t(q + 4, l16 + SM_QM + 512);
            if (wg) ldsm4t(k + 4, l16 + SM_QM + 1536);
            const uint32_t a2 = half_v(l16 + sb) + SM_SB + j * 256 + rank * 1280, mb = sb + MB_X;
            float s0[4], s1[4];
            mma16z(s0, q[0], q[1], q[2], q[3], k[0], k[1]);
            mma16z(s1, q[0], q[1], q[2], q[3], k[2], k[3]);
            float x = s0[0] + s1[2], y = s0[1] + s1[3];
            mma16z(s0, q[4], q[5], q[6], q[7], k[4], k[5]);
            mma16z(s1, q[4], q[5], q[6], q[7], k[6], k[7]);
            x += s0[0] + s1[2]; y += s0[1] + s1[3];
            if (SF16) {
              const uint32_t hv = pack_f16_sat(x, y), a3 = sb + (and_v(l16, 496u) >> 2) + SM_SB + j * 128 + rank * 640;
              st_async32(a3 + dl2, hv, mb + dl2); st_async32(a3 + dO, hv, mb + dO); sts32(a3, hv);
            } else {
              st_async64f(a2 + dl2, x, y, mb + dl2); st_async64f(a2 + dO, x, y, mb + dO); sts64f(a2, x, y);
            }
            bar_arrive(BAR_B, s + 1 < NSEG ? NB + 128 : NB);
            TR(4);
            if (HFPOS == 0 && wid == HRW) hint_fetch(s);
            tok_pair(k, 1, 3 + j);
            if (TOK7 ? (w == 1 || wg) : j < 3) tok_pair(k, 0, j);
          } else {
            if (!SMX_EARLY || wid == 7) bar_sync(BAR_B, s + 1 < NSEG ? NB + 128 : NB);
            if (TOK7 && wid == 7) {
              if (HFPOS == 0 && HRW == 7) hint_fetch(s);
              tok_pair(k, 0, 1);
            }
          }
        }
        if (wid == 5 || wid == 6) {
          if (s > 0) {
            const int g = s - 1, hf = wid - 5;
            if (!STPRE) mbar_wait(sb + MB_ST + 8 * (g & 1), (g >> 1) & 1);
            if (s == NSEG) bar_sync(BAR_QK, 96);
            const uint32_t st = half_v(l16 + sb) + (g & 1) * 4096 + rank * 1536 + hf * 256;
            const int ln = and_v(l16, 496u) >> 4;
            const int r0 = 16 * rank + 8 * hf + (ln >> 2) - 2 * (ln & 3);
            float p[5][2];
#pragma unroll
            for (int j = 0; j < 5; j++) {
              const float2 a = lds64f(st + SM_ST0 + j * 512), b = lds64f(st + SM_ST1 + j * 512);
              p[j][0] = a.x + b.x; p[j][1] = a.y + b.y;
              if (j > 0) {
                p[j][0] = 8 * (j - 1) > r0 ? -INFINITY : p[j][0];
                p[j][1] = 8 * (j - 1) + 1 > r0 ? -INFINITY : p[j][1];
              }
            }
            float m = fmaxf(fmaxf(fmaxf(p[0][0], p[0][1]), fmaxf(p[1][0], p[1][1])), fmaxf(fmaxf(p[2][0], p[2][1]), fmaxf(p[3][0], p[3][1])));
            m = fmaxf(m, fmaxf(p[4][0], p[4][1]));
            m = fmaxf(fmaxf(m, __shfl_xor_sync(~0u, m, 1)), fmaxf(__shfl_xor_sync(~0u, m, 2), __shfl_xor_sync(~0u, m, 3)));
#pragma unroll
            for (int j = 0; j < 5; j++) { p[j][0] = ex2(p[j][0] - m); p[j][1] = ex2(p[j][1] - m); }
            float l = (((p[0][0] + p[0][1]) + (p[1][0] + p[1][1])) + ((p[2][0] + p[2][1]) + (p[3][0] + p[3][1]))) + (p[4][0] + p[4][1]);
            l = rcp_fast((l + __shfl_xor_sync(~0u, l, 1)) + (__shfl_xor_sync(~0u, l, 2) + __shfl_xor_sync(~0u, l, 3)));
            const uint32_t pt = sb + dl2 + SM_PT + (g & 3) * 2560 + rank * 1280 + hf * 128 + ln * 4;
#pragma unroll
            for (int j = 0; j < 5; j++) st_async32(pt + j * 256, pack_bf16(p[j][0] * l, p[j][1] * l), sb + dl2 + MB_ST + 8 * (g & 1));
            TR(15);
          }
        } else if (s < NSEG) {
          fence_async_smem();
          TR(6);
          if (wid == 0) {
            bar_sync(BAR_HK, 192);
            if (s == NSEG - 1) bar_arrive(BAR_QK, 96);
            mbar_wait(sb + MB_X, s & 1);
            if (s + 1 < NSEG) mbar_wait(sb + MB_V + 8 * (s & 1), (s >> 1) & 1);
            if (lane == 0) {
              const uint32_t off = (s & 1) * 4096 + (rank ? 0 : 1536);
              bulk_s2c(sb + dO + SM_ST1 + off, sb + SM_ST0 + off, rank ? 1536 : 2560, sb + dO + MB_ST + 8 * (s & 1));
              mbar_expect(sb + MB_ST + 8 * (s & 1), rank ? 2560 : 1536);
              if (s + 3 < NSEG) mbar_expect(sb + MB_V + 8 * (s & 1), 8192);
              if (s + 1 < NSEG) mbar_expect(sb + MB_X, SBB + 2048);
            }
            __syncwarp();
          } else {
            bar_arrive(BAR_HK, 192);
            if (wid == HRW && s + 1 < NSEG) { if (HFPOS == 1) hint_fetch(s); hint_read(s); }
            if (wid == 3 && s + 4 < NSEG) {
              const uint32_t ln = and_v(l16, 496u) >> 4, g = s + 4, v = (head * 2 + rank) * 12 + ln;
              if (ln < 12) *reinterpret_cast<uint4*>(arb + (ar_off(g) + (v >> 3) * 256 + (v & 7) * 16)) = make_uint4(0, 0, 0, 0);
              if (ln == 12) *reinterpret_cast<uint32_t*>(arb + (hint_off(g) + (head * 2 + rank) * 4)) = 0;
              __syncwarp();
            }
            if (wid == 1 && s + 3 < NSEG) { if (XPOS == 1 || s == 0) mbar_wait(sb + MB_X, s & 1); if (lane == 0) load_x(s + 3, xb == 2 ? 0 : xb + 1); __syncwarp(); }
          }
        }
        if (s + 2 < NSEG) {
          float acc[16];
          x_wait();
          if (APRE == 3) load_a();
          TR(9);
          go();
          filler_mma(acc, xbuf(xb), IC<0>{}, IC<EXP_KS>{}, [&]() { if (STPRE) st_wait(); });
          x_next();
          epilogue(acc, s + 2);
        } else {
          if (s + 1 < NSEG) go();
          if (STPRE && s < NSEG) st_wait();
          if (APRE) load_a();
        }
        TR(8);
      }
    } else {
      auto epilogue = [&](const float* acc, int g) {
        const uint32_t dst = l16 + SM_PX + (g & 3) * 8192 + wid * 1024;
        stsm4(dst, pack_bf16(acc[0], acc[1]), pack_bf16(acc[2], acc[3]), pack_bf16(acc[4], acc[5]), pack_bf16(acc[6], acc[7]));
        stsm4(dst + 512, pack_bf16(acc[8], acc[9]), pack_bf16(acc[10], acc[11]), pack_bf16(acc[12], acc[13]), pack_bf16(acc[14], acc[15]));
        if (g < 2) fence_async_smem();
      };
#pragma unroll 1
      for (int g = 0; g < 2; g++) {
        float acc[16];
        x_wait(); filler_mma(acc, xbuf(xb), IC<0>{}, IC<36>{}, nop); x_next();
        if (g == 0) cluster_wait();
        epilogue(acc, g);
        if (g == 0) bar_arrive(BAR_GO, 384);
      }
      if (APRE == 3) load_a();
      if (tid == 0) TRG(2);
      unsigned char* oxp = ox + (size_t)head * 8192;
#pragma unroll 1
      for (int it = 0; it <= NSEG + 1; it++) {
        const int s = it < NSEG - 1 ? it : it == NSEG ? NSEG - 1 : NSEG;
        if (s < NSEG) {
          uint32_t lo, hi;
          mem_proj(s, 1.0f, lo, hi, nop);
          TR(2);
          const uint32_t a = half_v(l16 + sb) + SM_VM + ((s + 2) & 3) * 2048 + wid * 256, mb = sb + MB_X;
          st_async64(a + dl0, lo, hi, mb + dl0); st_async64(a + dl1, lo, hi, mb + dl1); sts64(a, lo, hi);
          if (s + 1 < NSEG) bar_arrive(BAR_B, 384);
          if (wid == 2) hint_fetch(s);
          TR(4);
        }
        if (it > 1) {
          const int g = it - 2, mt = wid & 1, eq = wid >> 1;
          uint32_t pm[2], p0[4], p1[4];
          const uint32_t pt = l16 + SM_PT + (g & 3) * 2560 + mt * 1280;
          mbar_wait(sb + MB_ST + 8 * (g & 1), (g >> 1) & 1);
          ldsm2(pm, pt); ldsm4(p0, pt + 256); ldsm4(p1, pt + 768);
          const uint32_t vma = half_v(l16 + sb) + SM_VM + ((g + 2) & 3) * 2048 + eq * 512;
          const uint2 bm0 = lds64(vma), bm1 = lds64(vma + 256);
          const uint32_t vx = l16 + and_v(l16, 384u) + SM_PX + (g & 3) * 8192 + eq * 2048;
          const int ln = and_v(l16, 496u) >> 4;
          const int row = 16 * mt + (ln & 15);
          const uint32_t os = sb + SM_OS + (g & 1) * 8192 + (eq >> 1) * 4096 + row * 128;
#pragma unroll
          for (int o2 = 0; o2 < 2; o2++) {
            float d[2][4];
            uint32_t bx[2][4];
            ldsm4(bx[0], vx + o2 * 1024); ldsm4(bx[1], vx + o2 * 1024 + 128);
            mma8z(d[0], pm[0], pm[1], o2 ? bm1.x : bm0.x);
            mma8z(d[1], pm[0], pm[1], o2 ? bm1.y : bm0.y);
            mma16(d[0], p0, bx[0][0], bx[0][1]); mma16(d[1], p0, bx[1][0], bx[1][1]);
            mma16(d[0], p1, bx[0][2], bx[0][3]); mma16(d[1], p1, bx[1][2], bx[1][3]);
            const int ch = (eq & 1) * 4 + o2 * 2 + (ln >> 4);
            stsm4(os + ((ch ^ (ln & 7)) << 4), pack_bf16(d[0][0], d[0][1]), pack_bf16(d[0][2], d[0][3]),
                  pack_bf16(d[1][0], d[1][1]), pack_bf16(d[1][2], d[1][3]));
          }
          fence_async_smem();
        }
        TR(6);
        auto publish = [&]() {
          if (tid == 32 && it >= 2) { bulk_wait0(); fence_async_global(); red_relaxed_add(&g_flags[it - 2], 1u); }
          __syncwarp();
        };
        if (wid == 1) {
          bar_sync(BAR_QK, 256);
          if (lane == 0 && it >= 2) { bulk_s2g(oxp + (size_t)(it - 2) * (NH * 8192), sb + SM_OS + (it & 1) * 8192, 8192); bulk_commit(); }
          __syncwarp();
        } else {
          if (s + 2 < NSEG) bar_arrive(BAR_QK, 256); else bar_sync(BAR_QK, 256);
          if (wid == 0 && s < NSEG) {
            mbar_wait(sb + MB_X, s & 1);
            if (lane == 0) {
              if (!VXB && s + 2 < NSEG) send_vx(s + 1, dl0);
              mbar_expect(sb + MB_ST + 8 * (s & 1), 2560);
              if (s + 1 < NSEG) mbar_expect(sb + MB_X, 2 * SBB);
            }
            __syncwarp();
          }
          if (wid == 7 && s + 3 < NSEG) { if (XPOS == 1 || s == 0) mbar_wait(sb + MB_X, s & 1); if (lane == 0) load_x(s + 3, xb == 2 ? 0 : xb + 1); __syncwarp(); }
          if (wid == 2 && s + 1 < NSEG) hint_read(s);
        }
        if (s + 2 < NSEG) {
          float acc[16];
          x_wait();
          if (APRE == 3) load_a();
          TR(9);
          go();
          filler_mma(acc, xbuf(xb), IC<0>{}, IC<EXP_KS>{}, publish);
          x_next();
          epilogue(acc, s + 2);
        } else {
          publish();
          if (s + 1 < NSEG) go();
          if (APRE) load_a();
        }
        TR(8);
      }
      if (tid == 32) TRG(7);
      __syncwarp();
    }
    TRDUMP();
    cluster_arrive();
    cluster_wait();
  } else {
    if (KSS < 5) asm volatile("setmaxnreg.dec.sync.aligned.u32 152;");
    const int t = tid - 256;
    if (tid == 256) {
    TRG(0);
    for (int i = 0; i < 3; i++) mbar_init(sb + MB_W + 8 * i, 1);
    mbar_init(sb + MB_WO, 1);
    mbar_init(sb + MB_XT, 1); mbar_init(sb + MB_XT + 8, 1); mbar_init(sb + MB_XT + 16, 1);
    mbar_init(sb + MB_X, 1);
    mbar_init(sb + MB_V, 1); mbar_init(sb + MB_V + 8, 1);
    mbar_init(sb + MB_ST, 1); mbar_init(sb + MB_ST + 8, 1);
    asm volatile("fence.mbarrier_init.release.cluster;" ::: "memory");
    fence_async_smem();
    mbar_expect(sb + MB_WO, 49152);
    for (int c = 0; c < 3; c++) mbar_expect(sb + MB_W + 8 * c, 2 * 24576);
    mbar_expect(sb + MB_X, rank < 2 ? SBB + 2048 : 2 * SBB);
    if (rank < 2) { mbar_expect(sb + MB_V, 8192); mbar_expect(sb + MB_V + 8, 8192); }
    sts32(sb + SM_ISC, 0x3f800000u); sts32(sb + SM_ZERO, 0); sts32(sb + SM_TP + 8, 0);
  }
    __syncwarp();
    bar_arrive(0, 384);
    bar_sync(BAR_O, 128);
    if (lane == 0 && w < 3) tma2d(sb + SM_XB + w * 16384, &tm_wo, rank * 192 + w * 64, head * DH, sb + MB_WO);
    __syncwarp();
    const uint32_t tag = (ld_relaxed(&g_epoch) + 1) & 0xffffu;
    if (w != HW) bar_arrive(BAR_MEM, 384);
    const uint32_t l16 = opaque(sb + lane * 16);
    const uint32_t vxo = (rank == 2 ? SM_PX : SM_VX) + w * 2048;
    const int vxm = rank == 2 ? 3 : 1;
    uint32_t va[2][2][4];
    auto load_va = [&](int g) {
      if (rank < 2 && g + 1 < NSEG) mbar_wait(sb + MB_V + 8 * (g & 1), (g >> 1) & 1);
      const uint32_t a = l16 + vxo + (g & vxm) * 8192;
      ldsm4(va[0][0], a); ldsm4(va[0][1], a + 512); ldsm4(va[1][0], a + 1024); ldsm4(va[1][1], a + 1536);
    };
    uint32_t WO[3][8][4];
    {
      if (t == 0) TRG(16);
      mbar_wait(sb + MB_WO, 0);
      if (t == 0) TRG(17);
      const int mat = lane >> 3, r = lane & 7;
#pragma unroll
      for (int tt = 0; tt < 3; tt++) {
        const int idx = 6 * w + 2 * tt + (mat & 1);
        const uint32_t base = sb + SM_XB + (idx >> 3) * 16384 + ((mat >> 1) * 8 + r) * 128 + (((idx & 7) ^ r) << 4);
#pragma unroll
        for (int ks = 0; ks < 8; ks++) ldsm4t(WO[tt][ks], base + ks * 2048);
      }
      float mx = 0.f;
#pragma unroll
      for (int tt = 0; tt < 3; tt++) {
        float n[4] = {0.f, 0.f, 0.f, 0.f};
#pragma unroll
        for (int ks = 0; ks < 8; ks++)
          mma16r(n, WO[tt][ks][0] & 0x7fff7fffu, WO[tt][ks][1] & 0x7fff7fffu, WO[tt][ks][2] & 0x7fff7fffu, WO[tt][ks][3] & 0x7fff7fffu, 0x3f803f80u, 0x3f803f80u);
        mx = fmaxf(mx, fmaxf(n[0], n[2]));
      }
      sts32(sb + SM_RED + (8 + w) * 4, __float_as_uint(warp_max_nn(mx)));
      if (t == 0) TRG(18);
      asm volatile("barrier.cluster.arrive.relaxed.aligned;" ::: "memory");
      asm volatile("barrier.cluster.wait.aligned;" ::: "memory");
      if (t == 0) TRG(19);
      if (lane == 0 && w < 2) load_x(w, w);
      __syncwarp();
      asm volatile("barrier.cluster.arrive.relaxed.aligned;" ::: "memory");
      {
        uint32_t xm = 0;
        const uint4* xp = reinterpret_cast<const uint4*>(xg + (size_t)(blockIdx.x & 63) * SEG * DM) + t;
#pragma unroll 1
        for (int r = 0; r < (blockIdx.x < NSEG ? 2 : 0); r++) {
          uint4 xv[9];
#pragma unroll
          for (int i = 0; i < 9; i++) xv[i] = __ldg(xp + (r * 9 + i) * 128);
#pragma unroll
          for (int i = 0; i < 9; i++) xm = babsmax2(babsmax2(xm, xv[i].x), babsmax2(babsmax2(xv[i].y, xv[i].z), xv[i].w));
        }
        sts32(sb + SM_XMAX + (8 + w) * 4, __reduce_max_sync(0xffffffffu, max(xm & 0xffffu, xm >> 16)));
      }
      if (t == 0) TRG(15);
      bar_sync(BAR_HK, 384);
      if (LDEP < 0) asm volatile("griddepcontrol.launch_dependents;" ::: "memory");
      uint32_t m0 = lds32(sb + SM_XMAX + min(lane, 11) * 4);
      const uint32_t xm0 = __reduce_max_sync(0xffffffffu, m0 & 0xffffu);
      m0 = __reduce_max_sync(0xffffffffu, m0 & 0xffff0000u);
      if (w == 0) {
        const uint32_t rv = lds32(sb + SM_RED + min(lane, 11) * 4);
        const uint32_t a = __reduce_max_sync(0xffffffffu, (rank == 2 && lane < 8) ? rv : 0u), b = __reduce_max_sync(0xffffffffu, lane >= 8 ? rv : 0u);
        const uint64_t rec = ((uint64_t)(((a + 0xffffu) & 0xffff0000u) | ((b + 0xffffu) >> 16)) << 32) | (xm0 << 16) | tag;
        if (lane == 0) asm volatile("st.relaxed.gpu.global.u64 [%0], %1;" ::"l"(&g_pub[blockIdx.x]), "l"(rec) : "memory");
      }
      cluster_wait();
      if (t == 32) load_x(2, 2);
      __syncwarp();
      if (rank == 2) {
        bar_sync(BAR_GO, 384);
        if (lane == 0 && w < 2) send_vx(0, w ? dl1 : dl0);
        __syncwarp();
      }
      bar_sync(BAR_O, 128);
      if (w == HW) {
        uint64_t rec[3];
        int lim = 0;
        while (true) {
#pragma unroll
          for (int i = 0; i < 3; i++) asm volatile("ld.relaxed.gpu.global.u64 %0, [%1];" : "=l"(rec[i]) : "l"(&g_pub[lane * 3 + i]) : "memory");
          const bool ok = ((uint32_t)rec[0] & 0xffffu) == tag && ((uint32_t)rec[1] & 0xffffu) == tag && ((uint32_t)rec[2] & 0xffffu) == tag;
          if (__all_sync(0xffffffffu, ok) || spin_fail(++lim, SPIN_LIMIT, 1)) break;
          __nanosleep(300);
        }
        const float w1 = __uint_as_float(__reduce_max_sync(0xffffffffu, (uint32_t)(rec[2] >> 32) & 0xffff0000u));
        float w2 = __uint_as_float(max(max((uint32_t)(rec[0] >> 32) << 16, (uint32_t)(rec[1] >> 32) << 16), (uint32_t)(rec[2] >> 32) << 16));
#pragma unroll
        for (int o = 16; o; o >>= 1) w2 += __shfl_xor_sync(~0u, w2, o);
        const float G = w1 * w2 * 1.1f;
#pragma unroll
        for (int i = 0; i < 3; i++)
          if (lane * 3 + i < NSEG) sts32(sb + SM_XMAX + (lane * 3 + i) * 4, __float_as_uint(__uint_as_float((uint32_t)rec[i] & 0xffff0000u) * G));
        sts32(sb + SM_G, __float_as_uint(G));
        sts32(sb + SM_MX + (lane & 3) * 4, __float_as_uint(__uint_as_float(m0) * G));
        if (lane == 0) TRG(3);
      }
      if (VAPOS < 2) load_va(0);
    }
    const uint32_t l8 = opaque(sb + lane * 8);
    auto hint_write = [&](int s) {
      uint32_t g;
      asm volatile("st.volatile.shared.b32 [%0], %1;" ::"r"(sb + SM_TP + 16), "r"(s) : "memory");
      const uint32_t c = clk32();
      uint32_t g0;
      asm volatile("mov.u32 %0, %%globaltimer_lo;" : "=r"(g0)::"memory");
      if (FINE) {
        int lim = 0;
        do { asm volatile("mov.u32 %0, %%globaltimer_lo;" : "=r"(g)::"memory"); } while (g == g0 && ++lim < 8);
        g = (g >> 2) - (((clk32() - c) * 9) >> 6);
      } else g = (g0 >> 5) << 3;
      sts64(sb + SM_TP, g, c);
      asm volatile("st.relaxed.gpu.global.u16 [%0], %1;" ::"l"(arb + hint_off(s) + blockIdx.x * 2),
                   "h"((unsigned short)((g - (rank == 2 ? R2SLACK * 8 : 0)) | 0x8000u)) : "memory");
    };
    if (w == HW) { bar_sync(BAR_MEM, 384); hint_write(0); }
#pragma unroll 1
    for (int sv_ = 0; sv_ < NSEG - 1; sv_++) {
      const int s = __shfl_sync(0xffffffffu, sv_, 0);
      TR(9);
      unsigned char* arw = arb + (uint32_t)(ar_off(s) + (rank * 8 + w * 2) * 1024 - sb + l16 + and_v(l16, 384u));
      bar_sync(BAR_O, 128);
      const float4 mx4 = lds128f(sb + SM_MX);
      const uint32_t zero = lds32(sb + SM_ZERO);
      const float bound = fmaxf(fmaxf(fmaxf(mx4.x, mx4.y), fmaxf(mx4.z, mx4.w)), __uint_as_float(lds32(sb + SM_XMAX + s * 4)));
      int e = (int)(__float_as_uint(bound) >> 23);
      e = min(max(e, 30), 230);
      sts64(sb + SM_ISC + ((s + 1) & 1) * 8, (uint32_t)(e - 14) << 23, (uint32_t)(127 + 14 + 127 - e) << 23);
      const uint32_t vma = l8 + SM_VM + ((s + 2) & 3) * 2048 + w * 512;
      if (VAPOS >= 2 && rank < 2) mbar_wait(sb + MB_V + 8 * (s & 1), (s >> 1) & 1);
      if (VAPOS == 3) { spin_until(lds32(sb + SM_TP + 4) + VAD, arw); load_va(s | 64); }
      bar_sync(BAR_B, rank < 2 ? NB + 128 : 384);
      if (VAPOS == 2) load_va(s | 64);
      mbar_wait_fast(sb + MB_X, s & 1);
      TR(11);
      float sv[10];
      uint2 vm0, vm1;
      if (SF16) {
        uint32_t h[10];
        ldsm4(h, l16 + SM_SB); ldsm4(h + 4, l16 + SM_SB + 512); ldsm2(h + 8, l16 + SM_SB + 1024);
#pragma unroll
        for (int j = 0; j < 5; j++) {
          const float2 a = __half22float2(*reinterpret_cast<const __half2*>(&h[j])), b = __half22float2(*reinterpret_cast<const __half2*>(&h[5 + j]));
          sv[2 * j] = a.x + b.x; sv[2 * j + 1] = a.y + b.y;
        }
      } else {
        float2 a[5], b[5];
#pragma unroll
        for (int j = 0; j < 5; j++) { a[j] = lds64f(l8 + SM_SB + j * 256); b[j] = lds64f(l8 + SM_SB + 1280 + j * 256); }
#pragma unroll
        for (int j = 0; j < 5; j++) { sv[2 * j] = a[j].x + b[j].x; sv[2 * j + 1] = a[j].y + b[j].y; }
      }
      float m = fmaxf(fmaxf(fmaxf(sv[0], sv[1]), fmaxf(sv[2], sv[3])), fmaxf(fmaxf(sv[4], sv[5]), fmaxf(sv[6], sv[7])));
      m = fmaxf(m, fmaxf(sv[8], sv[9]));
      {
        const float m1 = __shfl_xor_sync(~0u, m, 1), m2 = __shfl_xor_sync(~0u, m, 2), m3 = __shfl_xor_sync(~0u, m, 3);
        const uint32_t va2 = vma + (__float_as_uint(m) & zero);
        vm0 = lds64(va2); vm1 = lds64(va2 + 256);
        m = fmaxf(fmaxf(m, m1), fmaxf(m2, m3));
      }
      uint32_t pb[5];
#pragma unroll
      for (int j = 0; j < 5; j++) pb[j] = pack_bf16(ex2(sv[2 * j] - m), ex2(sv[2 * j + 1] - m));
      TR(12);
      float o0[4], o1[4], ls[4];
      const uint32_t ONE = 0x3f803f80u;
      mma8z(o0, vm0.x, vm0.y, pb[0]);
      mma8z(o1, vm1.x, vm1.y, pb[0]);
      mma8z(ls, ONE, ONE, pb[0]);
      mma16(o0, va[0][0], pb[1], pb[2]);
      mma16(o1, va[1][0], pb[1], pb[2]);
      mma16r(ls, ONE, ONE, ONE, ONE, pb[1], pb[2]);
      mma16(o0, va[0][1], pb[3], pb[4]);
      mma16(o1, va[1][1], pb[3], pb[4]);
      mma16r(ls, ONE, ONE, ONE, ONE, pb[3], pb[4]);
      stsm4(l16 + SM_OT + w * 512, pack_bf16(o0[0], o0[1]), pack_bf16(o0[2], o0[3]), pack_bf16(o1[0], o1[1]), pack_bf16(o1[2], o1[3]));
      bar_sync(BAR_O, 128 + (__float_as_uint(ls[2]) & zero));
      TR(13);
      float d[2][3][4];
      uint32_t b[4][4];
#pragma unroll
      for (int k2 = 0; k2 < 4; k2++) ldsm4t(b[k2], l16 + SM_OT + k2 * 512);
      const float r0 = rcp_fast(ls[0]), r1 = rcp_fast(ls[1]);
      const float sc1 = PIN ? 0.f : __uint_as_float(lds32(sb + SM_ISC + ((s + 1) & 1) * 8 + 4));
#pragma unroll
      for (int k2 = 0; k2 < 4; k2++) {
#pragma unroll
        for (int hh = 0; hh < 2; hh++)
#pragma unroll
          for (int tt = 0; tt < 3; tt++) {
            const uint32_t* a0 = WO[tt][2 * k2 + hh];
            if (k2 == 0) mma16z(d[hh][tt], a0[0], a0[1], a0[2], a0[3], b[k2][2 * hh], b[k2][2 * hh + 1]);
            else mma16(d[hh][tt], a0, b[k2][2 * hh], b[k2][2 * hh + 1]);
          }
      }
      if (GOCUT) {
        if (FPIN ? (__float_as_uint(sc1 * r0) & __float_as_uint(sc1 * r1)) == 0xffffffffu : s == 2000) __trap();
        bar_arrive(BAR_GO, GOCUT == 2 ? 384 : 256); if (GOCUT != 2) bar_arrive(BAR_GO + 1, 256);
        if (s == 2001) __trap();
      } else {
        const int cnt = 256 + ((__float_as_uint(d[0][0][0]) | __float_as_uint(d[0][1][0]) | __float_as_uint(d[0][2][0]) |
                                __float_as_uint(d[1][0][0]) | __float_as_uint(d[1][1][0]) | __float_as_uint(d[1][2][0])) & zero);
        bar_arrive(BAR_GO, cnt); bar_arrive(BAR_GO + 1, cnt);
      }
      const float sc2 = PIN ? __uint_as_float(lds32(sb + SM_ISC + ((s + 1) & 1) * 8 + 4)) : sc1;
      uint2 tp = lds64v(sb + SM_TP + 8);
      const float f0 = sc2 * r0, f1 = sc2 * r1;
      uint32_t h[6];
#pragma unroll
      for (int tt = 0; tt < 3; tt++) {
        h[2 * tt] = pack_f16(fmaf(d[1][tt][0], f0, d[0][tt][0] * f0), fmaf(d[1][tt][1], f1, d[0][tt][1] * f1));
        h[2 * tt + 1] = pack_f16(fmaf(d[1][tt][2], f0, d[0][tt][2] * f0), fmaf(d[1][tt][3], f1, d[0][tt][3] * f1));
      }
      red_f16x8(arw, h[0], h[1], h[2], 0x3c00u);
      red_f16x8(arw + 1024, h[3], h[4], h[5], 0x3c00u);
      TR(14);
      if (rank == 2 && w <= VXB && s + 2 < NSEG) {
        const uint32_t t0 = clk32();
        while (clk32() - t0 < VXD) {}
        if (lane == 0) send_vx(s + 1, w ? dl0 : dl1);
        __syncwarp();
      }
      const unsigned char* ar = arw + (w * 6 - rank * 8 - w * 2) * 1024;
      {
        int lim = 0;
        while (tp.x != (uint32_t)s + 1 && !spin_fail(++lim, SPIN_LIMIT * 16, 300 + s)) tp = lds64v(sb + SM_TP + 8);
        asm volatile("" ::: "memory");
        spin_until(tp.y, ar);
      }
      TR(6);
      uint32_t q[18];
      int lim = 0;
      uint4 v[6];
#pragma unroll
      for (int i = 0; i < 6; i++) v[i] = ld_relaxed_v4(ar + i * 1024);
      if (VAPOS == 1) load_va(s + 1);
      while (true) {
        uint32_t bad = 0;
        const uint32_t mb = l16 + SM_MEMB + w * 2304;
#pragma unroll
        for (int i = 0; i < 6; i++) {
          bad |= v[i].w ^ 0x5000u; q[3 * i] = h2b(v[i].x); q[3 * i + 1] = h2b(v[i].y); q[3 * i + 2] = h2b(v[i].z);
          if (i == 1) stsm4(mb, q[0], q[1], q[2], q[3]);
          if (i == 2) stsm4(mb + 512, q[4], q[5], q[6], q[7]);
          if (i == 3) stsm4(mb + 1024, q[8], q[9], q[10], q[11]);
          if (i == 5) { stsm4(mb + 1536, q[12], q[13], q[14], q[15]); stsm2(mb + 2048, q[16], q[17]); }
          if (SCUT && i < 5 && (i % (SCUT ? SCUT : 1)) == SCUT - 1) { if (s == 1000 + i) __trap(); }
        }
        if (!__any_sync(0xffffffffu, bad != 0) || spin_fail(++lim, SPIN_LIMIT, 100 + s)) break;
#pragma unroll
        for (int i = 0; i < 6; i++) if (!PRETRY || v[i].w != 0x5000u) v[i] = ld_relaxed_v4(ar + i * 1024);
      }
      if (w == HW) { bar_sync(BAR_MEM, 384); hint_write(s + 1); } else bar_arrive(BAR_MEM, 384);
      TR(8);
      TRP(0); TRV(3, lim);
      uint32_t mx = lds32(sb + SM_ZERO);
#pragma unroll
      for (int i = 0; i < 18; i++) mx = babsmax2(mx, q[i]);
      mx = __reduce_max_sync(0xffffffffu, max(mx << 16, mx & 0xffff0000u));
      sts32(sb + SM_MX + w * 4, __float_as_uint(__uint_as_float(mx) * __uint_as_float(lds32(sb + SM_ISC + ((s + 1) & 1) * 8)) * __uint_as_float(lds32(sb + SM_G))));
      if (s == LDEP) asm volatile("griddepcontrol.launch_dependents;" ::: "memory");
      if (t == 0 && s == 0) TRG(4);
      if (t == 0 && s == 62) TRG(5);
    }
    TRDUMP();
    if (t == 0) TRG(6);
    cluster_arrive();
    cluster_wait();
  }
}
constexpr int K2_CTAS = 36;
#define WPACE 500
__device__ __align__(1024) unsigned char g_h[32 * 18 * 8192];
__device__ __align__(256) uint4 g_part[4 * 9 * 4 * 4 * 3 * 128];
__device__ __align__(16) uint4 g_E[32 * DM];

#define TR2(i)
constexpr uint32_t S2_A = 0;
constexpr uint32_t S2_RING = 147456;
constexpr uint32_t S2_STG = S2_A + 9 * 8192;
constexpr uint32_t S2_MISC = S2_RING + 73728;
constexpr uint32_t MB2_FULL = S2_MISC, MB2_EMPTY = S2_MISC + 80, MB2_A = S2_MISC + 160, MB2_STG = S2_MISC + 168;
constexpr uint32_t K2_SMEM = S2_MISC + 256;
static_assert(K2_SMEM <= 232448, "smem2");

template <int TB>
DEVI void wg_n64_ss(float* d, uint64_t da, uint64_t db, int sc) {
  asm volatile("{.reg .pred p; setp.ne.b32 p, %34, 0;\n"
               "wgmma.mma_async.sync.aligned.m64n64k16.f32.bf16.bf16 {%0,%1,%2,%3,%4,%5,%6,%7,%8,%9,%10,%11,%12,%13,%14,%15,"
               "%16,%17,%18,%19,%20,%21,%22,%23,%24,%25,%26,%27,%28,%29,%30,%31}, %32, %33, p, 1, 1, 0, %35;}\n"
               : "+f"(d[0]), "+f"(d[1]), "+f"(d[2]), "+f"(d[3]), "+f"(d[4]), "+f"(d[5]), "+f"(d[6]), "+f"(d[7]),
                 "+f"(d[8]), "+f"(d[9]), "+f"(d[10]), "+f"(d[11]), "+f"(d[12]), "+f"(d[13]), "+f"(d[14]), "+f"(d[15]),
                 "+f"(d[16]), "+f"(d[17]), "+f"(d[18]), "+f"(d[19]), "+f"(d[20]), "+f"(d[21]), "+f"(d[22]), "+f"(d[23]),
                 "+f"(d[24]), "+f"(d[25]), "+f"(d[26]), "+f"(d[27]), "+f"(d[28]), "+f"(d[29]), "+f"(d[30]), "+f"(d[31])
               : "l"(da), "l"(db), "r"(sc), "n"(TB));
}
DEVI float2 cmul(float2 a, float2 b) { return make_float2(a.x * b.x - a.y * b.y, a.x * b.y + a.y * b.x); }
DEVI float2 cfma(float2 a, float2 b, float2 c) { return make_float2(fmaf(a.x, b.x, fmaf(-a.y, b.y, c.x)), fmaf(a.x, b.y, fmaf(a.y, b.x, c.y))); }
DEVI void wait_flag(const uint32_t* f, uint32_t target) {
  int lim = 0;
  while (ld_acquire(f) < target && !spin_fail(++lim, SPIN_LIMIT, 1000 + (uint32_t)(f - g_flags))) { __nanosleep(100); }
}

template <int MODE, int NKC, int NST>
DEVI void k2_mainloop(float* acc, uint32_t sb, uint32_t ph0, bool leader, int wg, bool first, bool last) {
  if (!first) bar_sync(4 + wg, 256);
  const uint64_t ds0 = mkdesc(sb + S2_RING, 16, 1024), dw0 = mkdesc(sb + S2_A, 16, 1024);
#pragma unroll
  for (int kc = 0; kc < NKC; kc++) {
    const int st = kc % NST;
    mbar_wait(sb + MB2_FULL + 8 * st, ph0 ^ (kc / NST));
    if (kc == NKC - 1 && !last) bar_arrive(5 - wg, 256);
    const uint64_t ds = ds0 + st * 512, dw = dw0 + kc * 512;
    WG_FENCE();
#pragma unroll
    for (int k = 0; k < 4; k++) {
      if (MODE == 0) wg_n64_ss<0>(acc, dw + 2 * k, ds + 2 * k, (kc | k) != 0);
      if (MODE == 1) wg_n64_ss<0>(acc, ds + 2 * k, dw + 2 * k, (kc | k) != 0);
      if (MODE == 2) wg_n64_ss<1>(acc, ds + 2 * k, dw + 128 * k, (kc | k) != 0);
    }
    WG_COMMIT();
    if (kc > 0) { WG_WAIT(1); if (leader) mbar_arrive(sb + MB2_EMPTY + 8 * ((kc - 1) % NST)); }
  }
  WG_WAIT(0);
  if (leader) mbar_arrive(sb + MB2_EMPTY + 8 * ((NKC - 1) % NST));
}

__global__ void __launch_bounds__(448, 1)
k_side(const __grid_constant__ CUtensorMap tm_xa, const __grid_constant__ CUtensorMap tm_wo,
       const bf16* __restrict__ xa, const bf16* __restrict__ lam_re, const bf16* __restrict__ lam_im,
       const bf16* __restrict__ b_re, const bf16* __restrict__ b_im, const bf16* __restrict__ c_re,
       const bf16* __restrict__ c_im, const bf16* __restrict__ log_dt, const bf16* __restrict__ dskip,
       float* __restrict__ out, const unsigned char* __restrict__ ox, unsigned char* __restrict__ hbuf) {
  extern __shared__ __align__(1024) unsigned char smem[];
  const uint32_t sb = smem_u32(smem);
  const int tid = threadIdx.x, lane = tid & 31;
  const int wid = __shfl_sync(0xffffffffu, tid >> 5, 0), wg = wid >> 2, w = wid & 3;
  const int cta = blockIdx.x;
  const int ct = cta >> 1, par = cta & 1;
  const int dt = cta >> 2, tq = cta & 3;
  if (tid == 0) {
    for (int i = 0; i < 9; i++) { mbar_init(sb + MB2_FULL + 8 * i, 1); mbar_init(sb + MB2_EMPTY + 8 * i, 4); }
    mbar_init(sb + MB2_A, 1); mbar_init(sb + MB2_STG, 1); mbar_init(sb + MB2_STG + 8, 1);
    fence_async_smem();
  }
  __syncthreads();

  if (wg == 2) {
    auto acquire = [&](int st, uint32_t ph) {
      mbar_wait(sb + MB2_EMPTY + 8 * st, ph ^ 1);
      mbar_expect(sb + MB2_FULL + 8 * st, 8192);
    };
    if (lane == 0) {
#pragma unroll 1
      for (int i = 0; i < 16; i++)
#pragma unroll 1
        for (int st = w; st < 9; st += 4) {
          acquire(st, i & 1);
          asm volatile("cp.async.bulk.tensor.5d.shared::cluster.global.mbarrier::complete_tx::bytes [%0], [%1, {%3, %4, %4, %4, %5}], [%2];"
                       ::"r"(sb + S2_RING + st * 8192), "l"(&tm_xa), "r"(sb + MB2_FULL + 8 * st), "r"(st * 64), "r"(0), "r"(2 * i + par) : "memory");
        }
    }
    __syncwarp();
    uint32_t ready = 0;
#pragma unroll 1
    for (int i = 0; i < 8; i++) {
      const int blk = tq + 4 * i;
      if (!((ready >> blk) & 1)) {
        int lim = 0;
        while (true) {
          ready = __ballot_sync(~0u, ld_acquire(&g_flags[64 + lane]) >= 18);
          if (((ready >> blk) & 1) || spin_fail(++lim, SPIN_LIMIT, 1064 + blk)) break;
          __nanosleep(100);
        }
        fence_async_global();
      }
      if (lane == 0) {
#pragma unroll 1
        for (int r = 0; r < 2; r++)
#pragma unroll 1
          for (int st = w; st < 9; st += 4) {
            acquire(st, r);
            bulk_g2s(sb + S2_RING + st * 8192, hbuf + ((size_t)blk * 18 + r * 9 + st) * 8192, 8192, sb + MB2_FULL + 8 * st);
          }
      }
      __syncwarp();
    }
    ready = 0;
#pragma unroll 1
    for (int blk = 0; blk < 32; blk++) {
      if (lane == 0) acquire(w, 0);
      __syncwarp();
      if (!((ready >> blk) & 1)) {
        int lim = 0;
        while (true) {
          const uint2 f = ld_relaxed_v2(&g_flags[2 * lane]);
          ready = __ballot_sync(~0u, f.x >= NH && f.y >= NH);
          if (((ready >> blk) & 1) || spin_fail(++lim, SPIN_LIMIT, 1000 + blk)) break;
          if (blk < 30) __nanosleep(300);
        }
        asm volatile("fence.acq_rel.cta;" ::: "memory");
        fence_async_global();
      }
      if (lane == 0) {
#pragma unroll
        for (int r = 0; r < 4; r++) {
          const int kc = w + 4 * r, st = kc & 7;
          if (r) acquire(st, r >> 1);
          const unsigned char* src = ox + ((size_t)(2 * blk) * NH + tq * 8) * 8192 + kc * 4096;
          bulk_g2s(sb + S2_RING + st * 8192, src, 4096, sb + MB2_FULL + 8 * st);
          bulk_g2s(sb + S2_RING + st * 8192 + 4096, src + NH * 8192, 4096, sb + MB2_FULL + 8 * st);
        }
      }
      __syncwarp();
    }
    return;
  }
  if (wg == 3) {
    const int g = w;
#pragma unroll 1
    for (int i = g; i < 16; i += 2) {
      const int c = 2 * i + par;
      bar_sync(6 + g, 160);
      if (lane == 0) {
        bulk_s2g(hbuf + ((size_t)c * 18 + ct) * 8192, sb + S2_STG + g * 8192, 8192);
        bulk_commit();
        bulk_wait_read0();
        mbar_arrive(sb + MB2_STG + 8 * g);
        bulk_wait0();
        fence_async_global();
        red_release_add(&g_flags[64 + c], 1u);
      }
      __syncwarp();
    }
    return;
  }
  const bool leader = lane == 0;
  TR2(0);
  float acc[32];
  for (int i = tid; i < 64 * 72; i += 256) {
    const int m = i / 72, c = i % 72;
    const bf16* src = ((m & 8) ? b_im : b_re) + (size_t)(ct * 32 + (m >> 4) * 8 + (m & 7)) * DM + c * 8;
    cp16(sb + S2_A + (c >> 3) * 8192 + m * 128 + (((c & 7) ^ (m & 7)) << 4), src);
  }
  auto load_c = [&](int kc0, int kc1) {
    for (int i = tid; i < 64 * 8 * (kc1 - kc0); i += 256) {
      const int per = 8 * (kc1 - kc0);
      const int d = i / per, r = i % per;
      const int ri = r / (per / 2), o = r % (per / 2);
      const int kc = kc0 + (o >> 2), c8 = (o & 3) * 2 + ri;
      const bf16* src = (ri ? c_im : c_re) + (size_t)(dt * 64 + d) * DM + kc0 * 32 + o * 8;
      cp16(sb + S2_A + kc * 8192 + d * 128 + ((c8 ^ (d & 7)) << 4), src);
    }
  };
  load_c(11, 18);
  const int q = lane & 3;
  const int p = ct * 32 + w * 8 + (lane >> 2);
  float2 lam, coef;
  {
    const float lr = __bfloat162float(lam_re[p]), li = __bfloat162float(lam_im[p]);
    const float dtv = __bfloat162float(__float2bfloat16(expf(__bfloat162float(log_dt[p]))));
    const float er = expf(dtv * lr);
    float sn, cs;
    sincosf(dtv * li, &sn, &cs);
    lam = make_float2(er * cs, er * sn);
    const float nr = lam.x - 1.0f, ni = lam.y, den = lr * lr + li * li;
    coef = make_float2((nr * lr + ni * li) / den, (ni * lr - nr * li) / den);
  }
  float2 L16 = cmul(lam, lam); L16 = cmul(L16, L16); L16 = cmul(L16, L16); L16 = cmul(L16, L16);
  const float2 L32 = cmul(L16, L16), L64 = cmul(L32, L32);
  const float2 Lq = q == 0 ? make_float2(1.f, 0.f) : q == 1 ? L16 : q == 2 ? L32 : cmul(L32, L16);
  const uint32_t tag = ld_relaxed(&g_epoch) + 1;
  cp_wait_all();
  fence_async_smem();
  bar_sync(1, 256);
  if (tid == 0) red_release_add(&g_flags[96], 1u);
  TR2(1);

  float2 H = make_float2(0.f, 0.f);
  int done = -1;
#pragma unroll 1
  for (int i = wg; i < 16; i += 2) {
    const int c = 2 * i + par;
    k2_mainloop<0, 9, 9>(acc, sb, wg, leader, wg, i == 0, false);
    TR2(8 + i);
    float2 e = make_float2(acc[0], acc[2]);
#pragma unroll
    for (int u = 1; u < 16; u++) e = cfma(lam, e, make_float2(acc[4 * (u >> 1) + (u & 1)], acc[4 * (u >> 1) + 2 + (u & 1)]));
    float2 tt;
    tt.x = __shfl_up_sync(~0u, e.x, 1); tt.y = __shfl_up_sync(~0u, e.y, 1);
    if (q >= 1) e = cfma(L16, tt, e);
    tt.x = __shfl_up_sync(~0u, e.x, 2); tt.y = __shfl_up_sync(~0u, e.y, 2);
    if (q >= 2) e = cfma(L32, tt, e);
    if (q == 3) {
      asm volatile("st.relaxed.gpu.global.v2.b64 [%0], {%1, %2};" ::"l"(&g_E[c * DM + p]),
                   "l"(((uint64_t)tag << 32) | __float_as_uint(e.x)), "l"(((uint64_t)tag << 32) | __float_as_uint(e.y)) : "memory");
    }
    float2 xq, Ec;
    xq.x = __shfl_up_sync(~0u, e.x, 1); xq.y = __shfl_up_sync(~0u, e.y, 1);
    if (q == 0) xq = make_float2(0.f, 0.f);
    Ec.x = __shfl_sync(~0u, e.x, lane | 3); Ec.y = __shfl_sync(~0u, e.y, lane | 3);
    for (int cc = done + 1; cc < c; cc++) {
      uint64_t a, b; int lim = 0;
      do {
        asm volatile("ld.relaxed.gpu.global.v2.b64 {%0, %1}, [%2];" : "=l"(a), "=l"(b) : "l"(&g_E[cc * DM + p]) : "memory");
      } while (((uint32_t)(a >> 32) != tag || (uint32_t)(b >> 32) != tag) && !spin_fail(++lim, SPIN_LIMIT, 2000 + cc));
      H = cfma(L64, H, make_float2(__uint_as_float((uint32_t)a), __uint_as_float((uint32_t)b)));
    }
    __syncwarp();
    float2 sst = cfma(Lq, H, xq);
    H = cfma(L64, H, Ec);
    done = c;
    mbar_wait(sb + MB2_STG + 8 * wg, ((i >> 1) & 1) ^ 1);
    const uint32_t stg = sb + S2_STG + wg * 8192;
    const uint32_t sa = stg + ((lane >> 4) * 8 + (lane & 7)) * 128 + (((2 * w + ((lane >> 3) & 1)) ^ (lane & 7)) << 4);
#pragma unroll
    for (int j2 = 0; j2 < 4; j2++) {
      uint32_t r[4];
#pragma unroll
      for (int jj = 0; jj < 2; jj++) {
        const int j = 2 * j2 + jj;
        sst = cfma(lam, sst, make_float2(acc[4 * j], acc[4 * j + 2]));
        const float2 h0 = cmul(coef, sst);
        sst = cfma(lam, sst, make_float2(acc[4 * j + 1], acc[4 * j + 3]));
        const float2 h1 = cmul(coef, sst);
        r[2 * jj] = pack_bf16(h0.x, h1.x);
        r[2 * jj + 1] = pack_bf16(-h0.y, -h1.y);
      }
      stsm4t(sa + j2 * 2048, r[0], r[1], r[2], r[3]);
    }
    fence_async_smem();
    bar_arrive(6 + wg, 160);
  }
  mbar_wait(sb + MB2_STG + 8 * wg, 1);
  bar_sync(1, 256);
  TR2(2);
  load_c(0, 11);
  cp_wait_all();
  fence_async_smem();
  bar_sync(1, 256);
  {
    float2 dsk[8];
#pragma unroll
    for (int j = 0; j < 8; j++) {
      const uint32_t v = *reinterpret_cast<const uint32_t*>(dskip + dt * 64 + j * 8 + 2 * q);
      dsk[j] = make_float2(bf_lo(v), bf_hi(v));
    }
#pragma unroll 1
    for (int i = wg; i < 8; i += 2) {
      const int blk = tq + 4 * i;
      k2_mainloop<1, 18, 9>(acc, sb, 0, leader, wg, false, false);
      TR2(24 + i);
#pragma unroll
      for (int hh = 0; hh < 2; hh++) {
        const int n = 16 * w + 8 * hh + (lane >> 2);
        const int tok = blk * 64 + ((n >> 1) & 3) * 16 + (n >> 3) * 2 + (n & 1);
        const bf16* xr = xa + (size_t)tok * DM + dt * 64 + 2 * q;
        float* orow = out + (size_t)tok * 1152 + dt * 64 + 2 * q;
#pragma unroll
        for (int j = 0; j < 8; j++) {
          const uint32_t xv = __ldg(reinterpret_cast<const uint32_t*>(xr + j * 8));
          const uint32_t sk = pack_bf16(bf_lo(xv) * dsk[j].x, bf_hi(xv) * dsk[j].y);
          __stcs(reinterpret_cast<float2*>(orow + j * 8), make_float2(2.f * acc[4 * j + 2 * hh] + bf_lo(sk), 2.f * acc[4 * j + 2 * hh + 1] + bf_hi(sk)));
        }
      }
    }
  }
  bar_sync(1, 256);
  TR2(3);
  if (tid == 0) {
    mbar_expect(sb + MB2_A, 131072);
    for (int b = 0; b < 8; b++) { tma2d(sb + S2_A + b * 16384, &tm_wo, dt * 64, tq * 1024 + b * 128, sb + MB2_A); __nanosleep(WPACE); }
    wait_flag(&g_flags[96], K2_CTAS);
  }
  bar_sync(1, 256);
  mbar_wait(sb + MB2_A, 0);
#pragma unroll 1
  for (int blk = wg; blk < 32; blk += 2) {
    k2_mainloop<2, 16, 8>(acc, sb, 0, leader, wg, false, blk == 31);
    TR2(32 + blk);
    if (blk == 31) {
#pragma unroll
      for (int hh = 0; hh < 2; hh++) {
        float* orow = out + (size_t)(blk * 64 + 16 * w + 8 * hh + (lane >> 2)) * 1152 + DM + dt * 64 + 2 * q;
#pragma unroll
        for (int j = 0; j < 8; j++)
          asm volatile("red.relaxed.gpu.global.add.v2.f32 [%0], {%1, %2};" ::"l"(orow + j * 8), "f"(acc[4 * j + 2 * hh]), "f"(acc[4 * j + 2 * hh + 1]) : "memory");
      }
      break;
    }
    const uint32_t rtag = tag * 32 + blk;
    uint4* pb = g_part + (size_t)((blk & 3) * 9 + dt) * (16 * 384) + (tid & 127);
    if (blk == 29) {
#pragma unroll
      for (int i = 0; i < 4; i++)
        *reinterpret_cast<float2*>(out + (size_t)(31 * 64 + 16 * w + 8 * (i >> 1) + (lane >> 2)) * 1152 + DM + dt * 64 + tq * 16 + (i & 1) * 8 + 2 * q) = make_float2(0.f, 0.f);
      __threadfence();
    }
    float own[8];
#pragma unroll
    for (int c = 0; c < 4; c++) {
      if (c != tq) {
        uint4* d = pb + (c * 4 + tq) * 384;
        st_relaxed_v4(d, __float_as_uint(acc[8 * c]), __float_as_uint(acc[8 * c + 1]), __float_as_uint(acc[8 * c + 2]), rtag);
        st_relaxed_v4(d + 128, __float_as_uint(acc[8 * c + 3]), __float_as_uint(acc[8 * c + 4]), __float_as_uint(acc[8 * c + 5]), rtag);
        st_relaxed_v4(d + 256, __float_as_uint(acc[8 * c + 6]), __float_as_uint(acc[8 * c + 7]), 0u, rtag);
      } else {
#pragma unroll
        for (int i = 0; i < 8; i++) own[i] = acc[8 * c + i];
      }
    }
    {
      uint4 r[9];
      int lim = 0;
      {
        __nanosleep(400);
        const uint4* pr = pb - lane + (tq * 4 + ((tq + 1 + min(lane, 2)) & 3)) * 384 + 256;
        while (__any_sync(0xffffffffu, ld_relaxed(&pr->w) != rtag) && !spin_fail(++lim, SPIN_LIMIT, 3100 + blk)) __nanosleep(400);
      }
      while (true) {
        uint32_t bad = 0;
#pragma unroll
        for (int i = 0; i < 9; i++) r[i] = ld_relaxed_v4(pb + (tq * 4 + ((tq + 1 + i / 3) & 3)) * 384 + (i % 3) * 128);
#pragma unroll
        for (int i = 0; i < 9; i++) bad |= r[i].w ^ rtag;
        if (!__any_sync(0xffffffffu, bad != 0) || spin_fail(++lim, SPIN_LIMIT, 3000 + blk)) break;
      }
#pragma unroll
      for (int i = 0; i < 3; i++) {
        own[0] += __uint_as_float(r[3 * i].x); own[1] += __uint_as_float(r[3 * i].y); own[2] += __uint_as_float(r[3 * i].z);
        own[3] += __uint_as_float(r[3 * i + 1].x); own[4] += __uint_as_float(r[3 * i + 1].y); own[5] += __uint_as_float(r[3 * i + 1].z);
        own[6] += __uint_as_float(r[3 * i + 2].x); own[7] += __uint_as_float(r[3 * i + 2].y);
      }
#pragma unroll
      for (int hh = 0; hh < 2; hh++) {
        float* orow = out + (size_t)(blk * 64 + 16 * w + 8 * hh + (lane >> 2)) * 1152 + DM + dt * 64 + tq * 16 + 2 * q;
#pragma unroll
        for (int j = 0; j < 2; j++) __stcs(reinterpret_cast<float2*>(orow + j * 8), make_float2(own[4 * j + 2 * hh], own[4 * j + 2 * hh + 1]));
      }
    }
  }
  if (cta == 0 && tid == 0) g_epoch = tag;
  TR2(4 + wg);
  asm volatile("griddepcontrol.wait;" ::: "memory");
}
typedef CUresult (*EncodeFn)(CUtensorMap*, CUtensorMapDataType, cuuint32_t, void*, const cuuint64_t*, const cuuint64_t*,
                             const cuuint32_t*, const cuuint32_t*, CUtensorMapInterleave, CUtensorMapSwizzle,
                             CUtensorMapL2promotion, CUtensorMapFloatOOBfill);
#define PROMO CU_TENSOR_MAP_L2_PROMOTION_L2_128B
static void make_map(EncodeFn fn, CUtensorMap* m, const void* p, int rank, const cuuint64_t* dims, const cuuint64_t* strides, const cuuint32_t* box) {
  cuuint32_t es[5] = {1, 1, 1, 1, 1};
  fn(m, CU_TENSOR_MAP_DATA_TYPE_BFLOAT16, rank, const_cast<void*>(p), dims, strides, box, es, CU_TENSOR_MAP_INTERLEAVE_NONE,
     CU_TENSOR_MAP_SWIZZLE_128B, PROMO, CU_TENSOR_MAP_FLOAT_OOB_FILL_NONE);
}

extern "C" void kernel_launch(void* const* d_in, const int* in_sizes, int n_in, void* d_out, int out_size) {
  static EncodeFn fn = nullptr;
  static void *p_ox = nullptr, *p_ar = nullptr, *p_h = nullptr;
  if (!fn) {
    cudaGetSymbolAddress(&p_ox, g_ox); cudaGetSymbolAddress(&p_ar, g_ar); cudaGetSymbolAddress(&p_h, g_h);
    void* p = nullptr;
    cudaDriverEntryPointQueryResult qr;
    cudaGetDriverEntryPoint("cuTensorMapEncodeTiled", &p, cudaEnableDefault, &qr);
    fn = (EncodeFn)p;
    cudaFuncSetAttribute(k_chain, cudaFuncAttributeMaxDynamicSharedMemorySize, K1_SMEM);
    cudaFuncSetAttribute(k_side, cudaFuncAttributeMaxDynamicSharedMemorySize, K2_SMEM);
  }
  const bf16* xa = (const bf16*)d_in[0];
  const bf16* xb = (const bf16*)d_in[9];
  CUtensorMap tx, tq, tk, tv, to, txa;
  {
    cuuint64_t d[2] = {DM, SEQ}, st[1] = {DM * 2}; cuuint32_t b[2] = {64, SEG};
    make_map(fn, &tx, xb, 2, d, st, b);
  }
  {
    cuuint64_t d[2] = {NH * DH, DM}, st[1] = {NH * DH * 2}; cuuint32_t b[2] = {64, 192};
    make_map(fn, &tq, d_in[11], 2, d, st, b); make_map(fn, &tk, d_in[12], 2, d, st, b); make_map(fn, &tv, d_in[13], 2, d, st, b);
  }
  {
    cuuint64_t d[2] = {DM, NH * DH}, st[1] = {DM * 2}; cuuint32_t b[2] = {64, 128};
    make_map(fn, &to, d_in[14], 2, d, st, b);
  }
  {
    cuuint64_t d[5] = {DM, 2, 4, 8, 32}, st[4] = {DM * 2, 16 * DM * 2, 2 * DM * 2, 64 * DM * 2}; cuuint32_t b[5] = {64, 2, 4, 8, 1};
    make_map(fn, &txa, xa, 5, d, st, b);
  }
  cudaStream_t stream = cudaStreamPerThread;
  {
    cudaLaunchConfig_t cfg = {};
    cfg.gridDim = dim3(K1_CTAS); cfg.blockDim = dim3(384); cfg.dynamicSmemBytes = K1_SMEM; cfg.stream = stream;
    cudaLaunchKernelEx(&cfg, k_chain, tx, tq, tk, tv, to, xb, (const bf16*)d_in[10], (unsigned char*)p_ox, (unsigned char*)p_ar);
  }
  {
    cudaLaunchConfig_t cfg = {};
    cfg.gridDim = dim3(K2_CTAS); cfg.blockDim = dim3(448); cfg.dynamicSmemBytes = K2_SMEM; cfg.stream = stream;
    cudaLaunchAttribute at[1];
    at[0].id = cudaLaunchAttributeProgrammaticStreamSerialization; at[0].val.programmaticStreamSerializationAllowed = 1;
    cfg.attrs = at; cfg.numAttrs = 1;
    cudaLaunchKernelEx(&cfg, k_side, txa, to, xa, (const bf16*)d_in[1], (const bf16*)d_in[2], (const bf16*)d_in[3], (const bf16*)d_in[4],
                       (const bf16*)d_in[5], (const bf16*)d_in[6], (const bf16*)d_in[7], (const bf16*)d_in[8], (float*)d_out,
                       (const unsigned char*)p_ox, (unsigned char*)p_h);
  }
}
```
